```python
import torch

def _softmax(x, axis=-1):
    return torch.softmax(x, dim=axis)
def _gelu(x):
    return torch.nn.functional.gelu(x, approximate="tanh")
def _silu(x):
    return torch.nn.functional.silu(x)
def _sigmoid(x):
    return torch.sigmoid(x)
def _layernorm(x, axis=-1, eps=1e-5):
    m = x.mean(dim=axis, keepdim=True)
    v = x.var(dim=axis, keepdim=True, unbiased=False)
    return (x - m) / torch.sqrt(v + eps)
def _scatter_add(tgt, idx, src, axis=0):
    return tgt.clone().index_add_(axis, idx, src)
def _segment_sum(src, seg, n):
    out = torch.zeros((n,) + src.shape[1:], dtype=src.dtype)
    return out.index_add_(0, seg, src)
def _pad(x, pw):
    flat = tuple(v for pair in reversed(pw) for v in pair)
    return torch.nn.functional.pad(x, flat)

kernel_name = 'sequential_preLN__gqa_block_cached__geglu_ffn__decode'

def setup_inputs():

    _w = (lambda a: (lambda t: t.to(torch.bfloat16) if t.is_floating_point() else t)(torch.as_tensor(a)))
    def _A_setup():
        B, Sq, D = 4, 1, 512
        Hq, Hkv, Sk, Dh = 32, 8, 8192, 128
        assert Hq % Hkv == 0, (Hq, Hkv)
        return {
            "x": _w((lambda *s: torch.randn(*s, dtype=torch.bfloat16) * 0.05)(B, Sq, D)),
            "k_cache": _w((lambda *s: torch.randn(*s, dtype=torch.bfloat16) * 3.2)(B, Hkv, Sk, Dh)),
            "v_cache": _w((lambda *s: torch.randn(*s, dtype=torch.bfloat16) * 0.4)(B, Hkv, Sk, Dh)),
            "wq": _w((lambda *s: torch.randn(*s, dtype=torch.bfloat16) * 3.2)(D, Hq * Dh) * (D ** -0.5)),
            "wo": _w((lambda *s: torch.randn(*s, dtype=torch.bfloat16) * 0.4)(Hq * Dh, D) * ((Hq * Dh) ** -0.5)),
        }
    _A_in = _A_setup()

    def _B_setup():
        B, S, D, F = 4, 1, 512, 1792
        return {
            "x": _w((lambda *s: torch.randn(*s, dtype=torch.bfloat16) * 0.05)(B, S, D)),
            "w_gate": _w((lambda *s: torch.randn(*s, dtype=torch.bfloat16) * 0.05)(D, F)),
            "w_up": _w((lambda *s: torch.randn(*s, dtype=torch.bfloat16) * 0.05)(D, F)),
            "w_down": _w((lambda *s: torch.randn(*s, dtype=torch.bfloat16) * 0.05)(F, D)),
        }
    _B_in = _B_setup()

    return {
        "A_x": _A_in["x"],
        "A_k_cache": _A_in["k_cache"],
        "A_v_cache": _A_in["v_cache"],
        "A_wq": _A_in["wq"],
        "A_wo": _A_in["wo"],
        "B_x": _B_in["x"],
        "B_w_gate": _B_in["w_gate"],
        "B_w_up": _B_in["w_up"],
        "B_w_down": _B_in["w_down"],
    }

def reference(A_x, A_k_cache, A_v_cache, A_wq, A_wo, B_x, B_w_gate, B_w_up, B_w_down):
    def _A_ref(x, k_cache, v_cache, wq, wo):
        B, Sq, D = x.shape
        Hq, Dh = 32, 128
        Hkv = k_cache.shape[1]
        rep = Hq // Hkv
        q = (lambda x, *d: x.permute(*d))((x @ wq).reshape(B, Sq, Hq, Dh), 0, 2, 1, 3)
        k = (lambda x, n, axis: torch.repeat_interleave(x, n, dim=axis))(k_cache, rep, axis=1)
        v = (lambda x, n, axis: torch.repeat_interleave(x, n, dim=axis))(v_cache, rep, axis=1)
        scores = torch.einsum("bhqd,bhkd->bhqk", q, k) * (Dh ** -0.5)
        p = _softmax(scores, axis=-1)
        o = torch.einsum("bhqk,bhkd->bhqd", p, v)
        return (lambda x, *d: x.permute(*d))(o, 0, 2, 1, 3).reshape(B, Sq, Hq * Dh) @ wo

    def _B_ref(x, w_gate, w_up, w_down):
        return (_gelu(x @ w_gate) * (x @ w_up)) @ w_down

    x = A_x
    h = x + _A_ref(_layernorm(x, axis=-1), A_k_cache, A_v_cache, A_wq, A_wo)
    h2 = h + _B_ref(_layernorm(h, axis=-1), B_w_gate, B_w_up, B_w_down)
    return h2
```

```cpp
#include <cuda_runtime.h>
#include <cuda_bf16.h>
#include <cuda.h>
#include <stdint.h>

namespace {

constexpr int NB = 4, DM = 512, HQ = 32, HKV = 8, SK = 8192, DH = 128, FF = 1792;
constexpr int NCTA = 128;
constexpr int NSPLIT = 4;
constexpr int TILE = 128;
constexpr int NTILE = SK / NSPLIT / TILE;
constexpr int SLOT_BYTES = 16384;
constexpr int NSLOT = 12;
constexpr int ITEM_WO = 2 + 4 * NTILE;
constexpr int ITEM_GU = ITEM_WO + 2;
constexpr int ITEM_WD = ITEM_WO + 4;
constexpr int NFCTA = FF / 16;
constexpr int HREP = 4;
constexpr int NCONS = 256;
#define NWARM 4
constexpr int NTHREADS = NCONS + 32 + 32 * NWARM;

#define WINDOW 4
#define WINDOW_T 2
#define TRIGGER 128
#define WARM_DELAY_NS 6000
#define INTERLEAVE 0

constexpr int SM_RING = 0;
constexpr int SM_MRG = NSLOT * SLOT_BYTES;
constexpr int SM_ML = SM_MRG + 8 * 4 * 136 * 4;
constexpr int SM_XN = SM_ML + 8 * 4 * 2 * 4;
constexpr int SM_QS = SM_XN + 4 * 520 * 2;
constexpr int SM_OF = SM_QS + 4 * 136 * 2;
constexpr int SM_ACT = SM_OF + 4 * 136 * 2;
constexpr int SM_BAR = SM_ACT + 4 * 24 * 2;
constexpr int SM_TOTAL = SM_BAR + 2 * NSLOT * 8;
constexpr int SMEM_BYTES = SM_TOTAL + 1024;

__device__ unsigned g_epoch;
__device__ unsigned g_count;
__device__ __align__(128) float g_q[NB * HQ * DH];
__device__ __align__(128) float g_po[NCTA * 4 * DH];
__device__ __align__(128) float g_pml[NCTA * 4 * 2];
__device__ __align__(128) float g_in1[NCTA * 32 * 16];
__device__ __align__(128) float g_h[HREP * NB * DM];
__device__ __align__(128) float g_in2[NCTA * NFCTA * 16];

#define TS(i) do {} while (0)
#define TSW(i) do {} while (0)

__device__ __forceinline__ uint32_t smem_u32(const void* p) { return (uint32_t)__cvta_generic_to_shared(p); }
__device__ __forceinline__ void mbar_init(uint32_t bar, uint32_t cnt) {
    asm volatile("mbarrier.init.shared::cta.b64 [%0], %1;" ::"r"(bar), "r"(cnt) : "memory");
}
__device__ __forceinline__ void mbar_expect_tx(uint32_t bar, uint32_t bytes) {
    asm volatile("mbarrier.arrive.expect_tx.shared::cta.b64 _, [%0], %1;" ::"r"(bar), "r"(bytes) : "memory");
}
__device__ __forceinline__ void mbar_arrive(uint32_t bar) {
    asm volatile("mbarrier.arrive.shared::cta.b64 _, [%0];" ::"r"(bar) : "memory");
}
constexpr uint32_t SPIN_LIMIT = 1u << 24;
__device__ __forceinline__ void mbar_wait(uint32_t bar, uint32_t parity) {
    uint32_t done = 0, it = 0;
    while (true) {
        asm volatile("{\n.reg .pred p;\nmbarrier.try_wait.parity.shared::cta.b64 p, [%1], %2;\nselp.u32 %0, 1, 0, p;\n}"
                     : "=r"(done) : "r"(bar), "r"(parity) : "memory");
        if (done) break;
        if (++it > SPIN_LIMIT) __trap();
    }
}
__device__ __forceinline__ void mbar_wait_p(uint32_t bar, uint32_t parity, uint32_t lv) {
    uint32_t it = 0;
    while (true) {
        uint32_t done;
        asm volatile("{\n.reg .pred p, q;\nsetp.ne.u32 q, %3, 0;\nsetp.eq.u32 p, %3, 0;\n"
                     "@q mbarrier.try_wait.parity.shared::cta.b64 p, [%1], %2;\nselp.u32 %0, 1, 0, p;\n}"
                     : "=r"(done) : "r"(bar), "r"(parity), "r"(lv) : "memory");
        if (done) break;
        if (++it > SPIN_LIMIT) __trap();
    }
}
__device__ __forceinline__ void tma2d(uint32_t dst, const CUtensorMap* tm, int c0, int c1, uint32_t bar, uint64_t pol) {
    asm volatile("cp.async.bulk.tensor.2d.shared::cluster.global.mbarrier::complete_tx::bytes.L2::cache_hint [%0], [%1, {%3, %4}], [%2], %5;"
                 ::"r"(dst), "l"(tm), "r"(bar), "r"(c0), "r"(c1), "l"(pol) : "memory");
}
__device__ __forceinline__ void tma3d(uint32_t dst, const CUtensorMap* tm, int c0, int c1, int c2, uint32_t bar, uint64_t pol) {
    asm volatile("cp.async.bulk.tensor.3d.shared::cluster.global.mbarrier::complete_tx::bytes.L2::cache_hint [%0], [%1, {%3, %4, %5}], [%2], %6;"
                 ::"r"(dst), "l"(tm), "r"(bar), "r"(c0), "r"(c1), "r"(c2), "l"(pol) : "memory");
}
__device__ __forceinline__ void ldsm4(uint32_t (&r)[4], uint32_t addr) {
    asm volatile("ldmatrix.sync.aligned.m8n8.x4.shared.b16 {%0,%1,%2,%3}, [%4];"
                 : "=r"(r[0]), "=r"(r[1]), "=r"(r[2]), "=r"(r[3]) : "r"(addr) : "memory");
}
__device__ __forceinline__ void ldsm4t(uint32_t (&r)[4], uint32_t addr) {
    asm volatile("ldmatrix.sync.aligned.m8n8.x4.trans.shared.b16 {%0,%1,%2,%3}, [%4];"
                 : "=r"(r[0]), "=r"(r[1]), "=r"(r[2]), "=r"(r[3]) : "r"(addr) : "memory");
}
__device__ __forceinline__ void mma16816(float (&c)[4], const uint32_t (&a)[4], uint32_t b0, uint32_t b1) {
    asm volatile("mma.sync.aligned.m16n8k16.row.col.f32.bf16.bf16.f32 {%0,%1,%2,%3}, {%4,%5,%6,%7}, {%8,%9}, {%0,%1,%2,%3};"
                 : "+f"(c[0]), "+f"(c[1]), "+f"(c[2]), "+f"(c[3])
                 : "r"(a[0]), "r"(a[1]), "r"(a[2]), "r"(a[3]), "r"(b0), "r"(b1));
}
__device__ __forceinline__ uint32_t movm_t(uint32_t a) {
    uint32_t d;
    asm volatile("movmatrix.sync.aligned.m8n8.trans.b16 %0, %1;" : "=r"(d) : "r"(a));
    return d;
}
__device__ __forceinline__ uint32_t pack_bf16(float lo, float hi) {
    uint32_t d;
    asm("cvt.rn.bf16x2.f32 %0, %1, %2;" : "=r"(d) : "f"(hi), "f"(lo));
    return d;
}
__device__ __forceinline__ float bf16r(float x) { return __bfloat162float(__float2bfloat16_rn(x)); }
__device__ __forceinline__ float bf_lo(uint32_t w) { return __uint_as_float(w << 16); }
__device__ __forceinline__ float bf_hi(uint32_t w) { return __uint_as_float(w & 0xffff0000u); }
__device__ __forceinline__ float ex2(float x) {
    float y;
    asm("ex2.approx.ftz.f32 %0, %1;" : "=f"(y) : "f"(x));
    return y;
}
__device__ __forceinline__ void cons_sync() { asm volatile("bar.sync 1, 256;" ::: "memory"); }
__device__ __forceinline__ void cons_sync_p(uint32_t lv) {
    asm volatile("{\n.reg .pred q;\nsetp.ne.u32 q, %0, 0;\n@q bar.sync 1, 256;\n}" ::"r"(lv) : "memory");
}
__device__ __forceinline__ void sts32(uint32_t a, float v, uint32_t p) {
    asm volatile("{\n.reg .pred q;\nsetp.ne.u32 q, %2, 0;\n@q st.shared.f32 [%0], %1;\n}" ::"r"(a), "f"(v), "r"(p) : "memory");
}
__device__ __forceinline__ void sts16(uint32_t a, uint16_t v, uint32_t p) {
    asm volatile("{\n.reg .pred q;\nsetp.ne.u32 q, %2, 0;\n@q st.shared.u16 [%0], %1;\n}" ::"r"(a), "h"(v), "r"(p) : "memory");
}
__device__ __forceinline__ void sts64(uint32_t a, uint32_t x, uint32_t y, uint32_t p) {
    asm volatile("{\n.reg .pred q;\nsetp.ne.u32 q, %3, 0;\n@q st.shared.v2.u32 [%0], {%1, %2};\n}" ::"r"(a), "r"(x), "r"(y), "r"(p) : "memory");
}
__device__ __forceinline__ void sts128f(uint32_t a, float x, float y, float z, float w, uint32_t p) {
    asm volatile("{\n.reg .pred q;\nsetp.ne.u32 q, %5, 0;\n@q st.shared.v4.f32 [%0], {%1, %2, %3, %4};\n}"
                 ::"r"(a), "f"(x), "f"(y), "f"(z), "f"(w), "r"(p) : "memory");
}
__device__ __forceinline__ float lds32(uint32_t a) {
    float v; asm volatile("ld.shared.f32 %0, [%1];" : "=f"(v) : "r"(a) : "memory"); return v;
}
__device__ __forceinline__ float2 lds64(uint32_t a) {
    float2 v; asm volatile("ld.shared.v2.f32 {%0, %1}, [%2];" : "=f"(v.x), "=f"(v.y) : "r"(a) : "memory"); return v;
}

__device__ __forceinline__ float tagf(float v, uint32_t tag) { return __uint_as_float((__float_as_uint(v) & ~1u) | tag); }
__device__ __forceinline__ void st_tag1(float* ptr, float v, uint32_t tag, uint32_t p) {
    asm volatile("{\n.reg .pred q;\nsetp.ne.u32 q, %2, 0;\n@q st.relaxed.gpu.global.f32 [%0], %1;\n}"
                 ::"l"(ptr), "f"(tagf(v, tag)), "r"(p) : "memory");
}
__device__ __forceinline__ void st_tag2(float* ptr, float a, float b, uint32_t tag, uint32_t p) {
    asm volatile("{\n.reg .pred q;\nsetp.ne.u32 q, %3, 0;\n@q st.relaxed.gpu.global.v2.f32 [%0], {%1, %2};\n}"
                 ::"l"(ptr), "f"(tagf(a, tag)), "f"(tagf(b, tag)), "r"(p) : "memory");
}
__device__ __forceinline__ void ld_rlx4(uint4& v, const float* ptr, uint32_t p) {
    asm volatile("{\n.reg .pred q;\nsetp.ne.u32 q, %5, 0;\n@q ld.relaxed.gpu.global.v4.u32 {%0,%1,%2,%3}, [%4];\n}"
                 : "+r"(v.x), "+r"(v.y), "+r"(v.z), "+r"(v.w) : "l"(ptr), "r"(p) : "memory");
}
__device__ __forceinline__ void ld_rlx2(uint2& v, const float* ptr, uint32_t p) {
    asm volatile("{\n.reg .pred q;\nsetp.ne.u32 q, %3, 0;\n@q ld.relaxed.gpu.global.v2.u32 {%0,%1}, [%2];\n}"
                 : "+r"(v.x), "+r"(v.y) : "l"(ptr), "r"(p) : "memory");
}
__device__ __forceinline__ uint32_t ld_rlx1(const unsigned* p) {
    uint32_t v;
    asm volatile("ld.relaxed.gpu.global.u32 %0, [%1];" : "=r"(v) : "l"(p) : "memory");
    return v;
}
__device__ __forceinline__ uint32_t bad4(const uint4& v, uint32_t tag) {
    uint32_t u, w, r;
    asm("lop3.b32 %0, %1, %2, %3, 0x7E;" : "=r"(u) : "r"(v.x), "r"(v.y), "r"(tag));
    asm("lop3.b32 %0, %1, %2, %3, 0x7E;" : "=r"(w) : "r"(v.z), "r"(v.w), "r"(tag));
    asm("lop3.b32 %0, %1, %2, 1, 0xA8;" : "=r"(r) : "r"(u), "r"(w));
    return r;
}
__device__ __forceinline__ uint32_t bad2(const uint2& v, uint32_t tag) {
    uint32_t u;
    asm("lop3.b32 %0, %1, %2, %3, 0x7E;" : "=r"(u) : "r"(v.x), "r"(v.y), "r"(tag));
    return u & 1u;
}
template <typename T> __device__ __forceinline__ void pin(T*& p) { asm volatile("" : "+l"(p)); }
__device__ __forceinline__ void pin(uint32_t& v) { asm volatile("" : "+r"(v)); }
__device__ __forceinline__ float sqrt_approx(float x) { float y; asm("sqrt.approx.ftz.f32 %0, %1;" : "=f"(y) : "f"(x)); return y; }
__device__ __forceinline__ float rcp_approx(float x) { float y; asm("rcp.approx.ftz.f32 %0, %1;" : "=f"(y) : "f"(x)); return y; }
template <int NK>
__device__ __forceinline__ void poll4(uint4 (&v)[NK], const float* src, uint32_t tag, uint32_t lv) {
    uint32_t bad[NK];
#pragma unroll
    for (int k = 0; k < NK; k++) { v[k] = make_uint4(tag, tag, tag, tag); bad[k] = lv; }
    uint32_t it = 0;
    while (true) {
#pragma unroll
        for (int k = 0; k < NK; k++) ld_rlx4(v[k], src + k * 128, bad[k]);
        uint32_t any = 0;
#pragma unroll
        for (int k = 0; k < NK; k++) { bad[k] = bad4(v[k], tag); any |= bad[k]; }
        if (!__any_sync(0xffffffffu, any)) break;
        if (++it > SPIN_LIMIT) __trap();
    }
}
__device__ __forceinline__ float u2f(uint32_t u) { return __uint_as_float(u); }

constexpr float LOG2E = 1.4426950408889634f;

__device__ __forceinline__ void warp_layernorm_store(const float (&v)[16], float c, uint32_t dst, uint32_t p) {
    float s1[4], s2[4];
#pragma unroll
    for (int k = 0; k < 4; k++) {
        const float d0 = v[4 * k] - c, d1 = v[4 * k + 1] - c, d2 = v[4 * k + 2] - c, d3 = v[4 * k + 3] - c;
        s1[k] = (d0 + d1) + (d2 + d3);
        s2[k] = fmaf(d0, d0, d1 * d1) + fmaf(d2, d2, d3 * d3);
    }
    float t1 = (s1[0] + s1[1]) + (s1[2] + s1[3]), t2 = (s2[0] + s2[1]) + (s2[2] + s2[3]);
#pragma unroll
    for (int o = 16; o > 0; o >>= 1) {
        t1 += __shfl_xor_sync(0xffffffffu, t1, o);
        t2 += __shfl_xor_sync(0xffffffffu, t2, o);
    }
    const float md = t1 * (1.f / 512.f);
    const float mean = bf16r(c + md);
    const float var = bf16r(fmaxf(fmaf(-md, md, t2 * (1.f / 512.f)), 0.f));
    const float inv = rcp_approx(bf16r(sqrt_approx(bf16r(var + 1e-5f))));
#pragma unroll
    for (int k = 0; k < 4; k++) {
        const uint32_t t01 = pack_bf16(v[4 * k + 0] - mean, v[4 * k + 1] - mean);
        const uint32_t t23 = pack_bf16(v[4 * k + 2] - mean, v[4 * k + 3] - mean);
        sts64(dst + k * 256, pack_bf16(bf_lo(t01) * inv, bf_hi(t01) * inv), pack_bf16(bf_lo(t23) * inv, bf_hi(t23) * inv), p);
    }
}

template <int NK>
__device__ __forceinline__ float inbox_reduce(const float* src, uint32_t tag, uint32_t lv, int lane) {
    uint4 v[NK];
    poll4<NK>(v, src, tag, lv);
    float a = 0.f, b = 0.f, c = 0.f, d = 0.f, a2 = 0.f, b2 = 0.f, c2 = 0.f, d2 = 0.f;
#pragma unroll
    for (int k = 0; k < NK; k += 2) {
        a += u2f(v[k].x); b += u2f(v[k].y); c += u2f(v[k].z); d += u2f(v[k].w);
        a2 += u2f(v[k + 1].x); b2 += u2f(v[k + 1].y); c2 += u2f(v[k + 1].z); d2 += u2f(v[k + 1].w);
    }
    a += a2; b += b2; c += c2; d += d2;
    const bool hi = lane & 16, h2 = lane & 8;
    float k0 = hi ? c : a, k1 = hi ? d : b;
    k0 += __shfl_xor_sync(0xffffffffu, hi ? a : c, 16);
    k1 += __shfl_xor_sync(0xffffffffu, hi ? b : d, 16);
    float kk = h2 ? k1 : k0;
    kk += __shfl_xor_sync(0xffffffffu, h2 ? k0 : k1, 8);
    kk += __shfl_xor_sync(0xffffffffu, kk, 4);
    return kk;
}

__global__ void __launch_bounds__(NTHREADS, 1)
fused_decode_kernel(const __grid_constant__ CUtensorMap tmK, const __grid_constant__ CUtensorMap tmV,
                    const __grid_constant__ CUtensorMap tmWq, const __grid_constant__ CUtensorMap tmWo,
                    const __grid_constant__ CUtensorMap tmWg, const __grid_constant__ CUtensorMap tmWu,
                    const __grid_constant__ CUtensorMap tmWd,
                    const __nv_bfloat16* __restrict__ x, __nv_bfloat16* __restrict__ out) {
    extern __shared__ uint8_t smem_raw[];
    const uint32_t sbase = (smem_u32(smem_raw) + 1023u) & ~1023u;
    const uint32_t bar_full = sbase + SM_BAR, bar_empty = bar_full + NSLOT * 8;
    const int tid = threadIdx.x, lane = tid & 31;
    const int c = blockIdx.x;

    if (tid == NCONS) {
        for (int i = 0; i < NSLOT; i++) { mbar_init(bar_full + 8 * i, 1); mbar_init(bar_empty + 8 * i, 4); }
        asm volatile("fence.mbarrier_init.release.cluster;" ::: "memory");
        asm volatile("fence.proxy.async.shared::cta;" ::: "memory");
    }
    __syncthreads();

    if ((tid >> 5) == 8) {
        if (lane == 0) {
            uint64_t pol_stream;
            asm volatile("createpolicy.fractional.L2::evict_first.b64 %0, 1.0;" : "=l"(pol_stream));
            const int g = c >> 2, s = c & 3;
            const int row0 = g * SK + (INTERLEAVE ? s * TILE : s * (SK / NSPLIT));
            const int rstep = INTERLEAVE ? NSPLIT * TILE : TILE;
            auto acquire = [&](int i, int window) {
                if (i >= NSLOT) mbar_wait(bar_empty + 8 * (i % NSLOT), ((i / NSLOT) - 1) & 1);
                if (i >= window) { const int j = i - window; mbar_wait(bar_full + 8 * (j % NSLOT), (j / NSLOT) & 1); }
            };
            mbar_expect_tx(bar_full, SLOT_BYTES);
            tma2d(sbase, &tmWq, 32 * c, 0, bar_full, pol_stream);
            mbar_expect_tx(bar_full + 8, SLOT_BYTES);
            tma2d(sbase + SLOT_BYTES, &tmWq, 32 * c, 256, bar_full + 8, pol_stream);
#pragma unroll 1
            for (int i = 2; i < ITEM_WO; i++) {
                const int slot = i % NSLOT;
                acquire(i, WINDOW);
                const int t = (i - 2) >> 2, sub = (i - 2) & 3;
                mbar_expect_tx(bar_full + 8 * slot, SLOT_BYTES);
                tma3d(sbase + slot * SLOT_BYTES, (sub & 2) ? &tmV : &tmK, 0, row0 + t * rstep + (sub & 1) * 64, 0,
                      bar_full + 8 * slot, pol_stream);
            }
            TS(1);
            const unsigned epoch = ld_rlx1(&g_epoch);
            asm volatile("red.relaxed.gpu.global.add.u32 [%0], 1;" ::"l"(&g_count) : "memory");
            if (TRIGGER > 0) {
                uint32_t it = 0;
                while ((int)(ld_rlx1(&g_count) - epoch * NCTA) < TRIGGER) {
                    __nanosleep(40);
                    if (++it > SPIN_LIMIT) __trap();
                }
            }
            TS(2);
#pragma unroll 1
            for (int hf = 0; hf < 2; hf++) {
                const int i = ITEM_WO + hf, slot = i % NSLOT;
                acquire(i, WINDOW_T);
                mbar_expect_tx(bar_full + 8 * slot, SLOT_BYTES);
                tma3d(sbase + slot * SLOT_BYTES, &tmWo, 0, 128 * (c >> 2), 2 * (c & 3) + hf, bar_full + 8 * slot, pol_stream);
            }
            if (c < NFCTA) {
#pragma unroll 1
                for (int hf = 0; hf < 2; hf++) {
                    const int i = ITEM_GU + hf, slot = i % NSLOT;
                    acquire(i, WINDOW_T);
                    const uint32_t fb = bar_full + 8 * slot, dst = sbase + slot * SLOT_BYTES;
                    mbar_expect_tx(fb, SLOT_BYTES);
                    tma2d(dst, &tmWg, 16 * c, 256 * hf, fb, pol_stream);
                    tma2d(dst + 8192, &tmWu, 16 * c, 256 * hf, fb, pol_stream);
                }
#pragma unroll 1
                for (int hf = 0; hf < 2; hf++) {
                    const int i = ITEM_WD + hf, slot = i % NSLOT;
                    acquire(i, WINDOW_T);
                    mbar_expect_tx(bar_full + 8 * slot, 8192);
                    tma3d(sbase + slot * SLOT_BYTES, &tmWd, 0, 16 * c, 4 * hf, bar_full + 8 * slot, pol_stream);
                }
            }
            TS(14);
        }
        return;
    }

    uint32_t lv;
    asm volatile("mov.u32 %0, %1;" : "=r"(lv) : "r"((tid < NCONS) ? 1u : 0u));
    const int warp = lv ? (tid >> 5) : 0;
    const int vtid = warp * 32 + lane;
    const int r = lane >> 2, t4 = lane & 3;
    const int wg = warp >> 2, wl = warp & 3;
    const uint32_t s_red = sbase + SM_MRG, s_ml = sbase + SM_ML, s_xn = sbase + SM_XN;
    const uint32_t s_qs = sbase + SM_QS, s_of = sbase + SM_OF, s_act = sbase + SM_ACT;
    const int brow = lane & 3, bch = lane >> 3;

    const uint32_t tag = (ld_rlx1(&g_epoch) & 1u) ^ 1u;

    const int red_b = 2 * (c >> 6) + ((lane >> 3) & 1);
    const int red_n = 8 * (c & 63) + 2 * t4 + ((lane >> 4) & 1);
    const float x_res = __bfloat162float(x[red_b * DM + red_n]);

    float* p_po = &g_po[(c * 4 + (vtid >> 6)) * DH + (vtid & 63) * 2];
    float* p_pml = &g_pml[(c * 4 + (vtid >> 6)) * 2];
    const int cta0 = ((warp & 3) * 8 + (c >> 4)) * 4, hh = (c >> 2) & 3;
    const float* q_po = &g_po[(cta0 * 4 + hh) * DH + lane * 4];
    const float* q_pml = &g_pml[(cta0 * 4 + hh) * 2];
    float* p_in1 = &g_in1[((t4 * 64 + 16 * (c & 3) + 2 * warp) * 32 + (c >> 2)) * 16 + 2 * r];
    const float* q_in1 = &g_in1[(c * 32 + r) * 16 + 4 * t4];
    float* p_h = &g_h[((lane & 4) ? HREP / 2 : 0) * (NB * DM) + red_b * DM + red_n];
    const float* q_h = &g_h[(c % HREP) * (NB * DM) + (warp & 3) * DM + lane * 4];
    float* p_in2 = &g_in2[((t4 * 64 + 8 * warp) * NFCTA + (c < NFCTA ? c : 0)) * 16 + 2 * r];
    const float* q_in2 = &g_in2[(c * NFCTA + r) * 16 + 4 * t4];
    __nv_bfloat16* p_out = out + red_b * DM + red_n;
    pin(p_po); pin(p_pml); pin(q_po); pin(q_pml); pin(p_in1); pin(q_in1); pin(p_h); pin(q_h); pin(p_in2); pin(q_in2); pin(p_out);

    float o[8][4];
#pragma unroll
    for (int j = 0; j < 8; j++) { o[j][0] = o[j][1] = o[j][2] = o[j][3] = 0.f; }
    float m0 = -INFINITY, m1 = -INFINITY, l0 = 0.f, l1 = 0.f;

    if (lv) {
        if (warp < NB) {
            float v[16];
#pragma unroll
            for (int k = 0; k < 4; k++) {
                uint2 w = *reinterpret_cast<const uint2*>(x + warp * DM + k * 128 + lane * 4);
                v[4 * k + 0] = bf_lo(w.x); v[4 * k + 1] = bf_hi(w.x); v[4 * k + 2] = bf_lo(w.y); v[4 * k + 3] = bf_hi(w.y);
            }
            warp_layernorm_store(v, __shfl_sync(0xffffffffu, v[0], 0), s_xn + warp * 1040 + lane * 8, 1u);
        }
        cons_sync();

        mbar_wait(bar_full + 8 * wg, 0);
        TSW(3);
        {
            float acc[2][4] = {};
#pragma unroll
            for (int kp = 0; kp < 2; kp++) {
                uint32_t b[4];
                ldsm4(b, s_xn + brow * 1040 + (warp * 64 + kp * 32 + bch * 8) * 2);
#pragma unroll
                for (int k2 = 0; k2 < 2; k2++) {
                    const int krow = warp * 64 + kp * 32 + k2 * 16 + (lane & 7) + ((lane >> 4) << 3);
#pragma unroll
                    for (int mt = 0; mt < 2; mt++) {
                        const int chunk = mt * 2 + ((lane >> 3) & 1);
                        uint32_t a[4];
                        ldsm4t(a, sbase + krow * 64 + ((chunk ^ ((krow >> 1) & 3)) << 4));
                        mma16816(acc[mt], a, b[2 * k2], b[2 * k2 + 1]);
                    }
                }
            }
            __syncwarp();
            if (lane == 0) mbar_arrive(bar_empty + 8 * wg);
            const uint32_t pw = t4 < 2;
#pragma unroll
            for (int mt = 0; mt < 2; mt++) {
                const uint32_t dst = s_red + (warp * 144 + (2 * t4) * 36 + mt * 16 + r) * 4;
                sts32(dst, acc[mt][0], pw); sts32(dst + 144, acc[mt][1], pw);
                sts32(dst + 32, acc[mt][2], pw); sts32(dst + 144 + 32, acc[mt][3], pw);
            }
            cons_sync();
            if (tid < 128) {
                float s = 0.f;
#pragma unroll
                for (int w = 0; w < 8; w++) s += lds32(s_red + (w * 144 + warp * 36 + lane) * 4);
                st_tag1(&g_q[warp * (HQ * DH) + 32 * c + lane], bf16r(s), tag, 1u);
                const int g = c >> 2;
                const float* src = &g_q[(g >> 3) * (HQ * DH) + (g & 7) * 512 + tid * 4];
                uint4 v;
                uint32_t it = 0;
                while (true) {
                    ld_rlx4(v, src, 1u);
                    if (!(bad4(v, tag) & 1)) break;
                    if (++it > SPIN_LIMIT) __trap();
                }
                sts64(s_qs + (warp * 136 + lane * 4) * 2, (v.x >> 16) | (v.y & 0xffff0000u), (v.z >> 16) | (v.w & 0xffff0000u), 1u);
            }
            cons_sync();
            TSW(4);
        }

        uint32_t qf[8][2];
#pragma unroll
        for (int j = 0; j < 8; j += 2) {
            uint32_t b[4];
            ldsm4(b, s_qs + brow * 272 + (j * 16 + bch * 8) * 2);
            qf[j][0] = b[0]; qf[j][1] = b[1]; qf[j + 1][0] = b[2]; qf[j + 1][1] = b[3];
        }
        const int krow = wl * 16 + (lane & 7) + (((lane >> 3) & 1) << 3);
        const int kch = lane >> 4;
        const int vrow = wl * 16 + (lane & 7) + ((lane >> 4) << 3);
        const int vch = (lane >> 3) & 1;
        const float scale = 0.08838834764831845f;

#pragma unroll 1
        for (int t = 0; t < NTILE; t++) {
            const int ik = 2 + 4 * t + wg, iv = ik + 2;
            const int sk = ik % NSLOT, sv = iv % NSLOT;
            mbar_wait(bar_full + 8 * sk, (ik / NSLOT) & 1);
            float sa[4] = {0.f, 0.f, 0.f, 0.f}, sb[4] = {0.f, 0.f, 0.f, 0.f};
            const uint32_t kb = sbase + sk * SLOT_BYTES + krow * 128;
#pragma unroll
            for (int j = 0; j < 8; j += 2) {
                uint32_t a0[4], a1[4];
                ldsm4(a0, kb + (j >> 2) * 8192 + (((((j & 3) << 1) + kch) ^ (krow & 7)) << 4));
                ldsm4(a1, kb + ((j + 1) >> 2) * 8192 + ((((((j + 1) & 3) << 1) + kch) ^ (krow & 7)) << 4));
                mma16816(sa, a0, qf[j][0], qf[j][1]);
                mma16816(sb, a1, qf[j + 1][0], qf[j + 1][1]);
            }
            __syncwarp();
            if (lane == 0) mbar_arrive(bar_empty + 8 * sk);
            const float s0 = bf16r(bf16r(sa[0] + sb[0]) * scale), s1 = bf16r(bf16r(sa[1] + sb[1]) * scale);
            const float s2 = bf16r(bf16r(sa[2] + sb[2]) * scale), s3 = bf16r(bf16r(sa[3] + sb[3]) * scale);
            float x0 = fmaxf(s0, s2), x1 = fmaxf(s1, s3);
#pragma unroll
            for (int off = 4; off < 32; off <<= 1) {
                x0 = fmaxf(x0, __shfl_xor_sync(0xffffffffu, x0, off));
                x1 = fmaxf(x1, __shfl_xor_sync(0xffffffffu, x1, off));
            }
            if (__any_sync(0xffffffffu, (x0 > m0) || (x1 > m1))) {
                const float n0 = fmaxf(m0, x0), n1 = fmaxf(m1, x1);
                const float a0 = ex2((m0 - n0) * LOG2E), a1 = ex2((m1 - n1) * LOG2E);
                m0 = n0; m1 = n1;
                l0 *= a0; l1 *= a1;
#pragma unroll
                for (int j = 0; j < 8; j++) { o[j][0] *= a0; o[j][1] *= a1; o[j][2] *= a0; o[j][3] *= a1; }
            }
            const float p0 = ex2((s0 - m0) * LOG2E), p1 = ex2((s1 - m1) * LOG2E);
            const float p2 = ex2((s2 - m0) * LOG2E), p3 = ex2((s3 - m1) * LOG2E);
            l0 += p0 + p2; l1 += p1 + p3;
            const uint32_t pb0 = movm_t(pack_bf16(p0, p1));
            const uint32_t pb1 = movm_t(pack_bf16(p2, p3));

            mbar_wait(bar_full + 8 * sv, (iv / NSLOT) & 1);
            const uint32_t vb = sbase + sv * SLOT_BYTES + vrow * 128;
#pragma unroll
            for (int j = 0; j < 8; j++) {
                uint32_t a[4];
                ldsm4t(a, vb + (j >> 2) * 8192 + (((((j & 3) << 1) + vch) ^ (vrow & 7)) << 4));
                mma16816(o[j], a, pb0, pb1);
            }
            __syncwarp();
            if (lane == 0) mbar_arrive(bar_empty + 8 * sv);
        }
        TSW(5);
    } else {
        __nanosleep(WARM_DELAY_NS);
        const int wt = tid - (NCONS + 32);
        const float z = __uint_as_float(tag ^ 1u);
        auto st4 = [&](float* p) {
            asm volatile("st.relaxed.gpu.global.v4.f32 [%0], {%1, %1, %1, %1};" ::"l"(p), "f"(z) : "memory");
        };
        for (int i = wt; i < 128; i += 32 * NWARM) {
            st4(&g_po[c * 512 + i * 4]);
            const int seg = i >> 2;
            st4(&g_in1[(((seg >> 4) * 64 + 16 * (c & 3) + (seg & 15)) * 32 + (c >> 2)) * 16 + (i & 3) * 4]);
        }
        if (c < NFCTA)
            for (int i = wt; i < 512; i += 32 * NWARM) st4(&g_in2[((i >> 2) * NFCTA + c) * 16 + (i & 3) * 4]);
        if (wt < 16) st4(&g_h[(wt >> 2) * (NB * DM) + (2 * (c >> 6) + ((wt >> 1) & 1)) * DM + 8 * (c & 63) + (wt & 1) * 4]);
        else if (wt < 18) st4(&g_pml[c * 8 + (wt - 16) * 4]);
        asm volatile("bar.arrive 2, %0;" ::"n"(NCONS + 32 * NWARM) : "memory");
    }

    const uint32_t pw = lv && (t4 < 2);

    {
#pragma unroll
        for (int off = 4; off < 32; off <<= 1) {
            l0 += __shfl_xor_sync(0xffffffffu, l0, off);
            l1 += __shfl_xor_sync(0xffffffffu, l1, off);
        }
        const uint32_t dst = s_red + (warp * 544 + (2 * t4) * 136 + r) * 4;
#pragma unroll
        for (int j = 0; j < 8; j++) {
            sts32(dst + j * 64, o[j][0], pw);
            sts32(dst + 544 + j * 64, o[j][1], pw);
            sts32(dst + j * 64 + 32, o[j][2], pw);
            sts32(dst + 544 + j * 64 + 32, o[j][3], pw);
        }
        sts128f(s_ml + (warp * 8 + t4 * 4) * 4, m0, l0, m1, l1, pw && r == 0);
        asm volatile("{\n.reg .pred q;\nsetp.ne.u32 q, %0, 0;\n@q bar.sync 2, %1;\n}" ::"r"(lv), "n"(NCONS + 32 * NWARM) : "memory");
        TSW(18);
        const int h = vtid >> 6, d = (vtid & 63) * 2;
        float2 ml[8];
#pragma unroll
        for (int w = 0; w < 8; w++) ml[w] = lds64(s_ml + (w * 8 + h * 2) * 4);
        float M = ml[0].x;
#pragma unroll
        for (int w = 1; w < 8; w++) M = fmaxf(M, ml[w].x);
        float a0 = 0.f, a1 = 0.f, L = 0.f;
#pragma unroll
        for (int w = 0; w < 8; w++) {
            const float sc = ex2((ml[w].x - M) * LOG2E);
            const float2 ov = lds64(s_red + (w * 544 + h * 136 + d) * 4);
            a0 = fmaf(sc, ov.x, a0); a1 = fmaf(sc, ov.y, a1); L = fmaf(sc, ml[w].y, L);
        }
        st_tag2(p_po, a0, a1, tag, lv);
        st_tag2(p_pml, M, L, tag, lv && (vtid & 63) == 0);
        TSW(6);
    }

    {
        if (warp < NB) {
            uint4 ov[4]; uint2 ml[4];
            uint32_t bo[4], bm[4];
#pragma unroll
            for (int s = 0; s < 4; s++) { ov[s] = make_uint4(tag, tag, tag, tag); ml[s] = make_uint2(tag, tag); bo[s] = bm[s] = lv; }
            uint32_t it = 0;
            while (true) {
#pragma unroll
                for (int s = 0; s < 4; s++) {
                    ld_rlx4(ov[s], q_po + s * 4 * DH, bo[s]);
                    ld_rlx2(ml[s], q_pml + s * 8, bm[s]);
                }
                uint32_t any = 0;
#pragma unroll
                for (int s = 0; s < 4; s++) { bo[s] = bad4(ov[s], tag); bm[s] = bad2(ml[s], tag); any |= bo[s] | bm[s]; }
                if (!__any_sync(0xffffffffu, any)) break;
                if (++it > SPIN_LIMIT) __trap();
            }
            TSW(19);
            const float M = fmaxf(fmaxf(u2f(ml[0].x), u2f(ml[1].x)), fmaxf(u2f(ml[2].x), u2f(ml[3].x)));
            float L = 0.f, a0 = 0.f, a1 = 0.f, a2 = 0.f, a3 = 0.f;
#pragma unroll
            for (int s = 0; s < 4; s++) {
                const float sc = ex2((u2f(ml[s].x) - M) * LOG2E);
                L = fmaf(sc, u2f(ml[s].y), L);
                a0 = fmaf(sc, u2f(ov[s].x), a0); a1 = fmaf(sc, u2f(ov[s].y), a1);
                a2 = fmaf(sc, u2f(ov[s].z), a2); a3 = fmaf(sc, u2f(ov[s].w), a3);
            }
            const float inv = rcp_approx(L);
            sts64(s_of + (warp * 136 + lane * 4) * 2, pack_bf16(a0 * inv, a1 * inv), pack_bf16(a2 * inv, a3 * inv), lv);
        }
        cons_sync_p(lv);
        TSW(7);
        const int slot = (ITEM_WO + wg) % NSLOT;
        mbar_wait_p(bar_full + 8 * slot, ((ITEM_WO + wg) / NSLOT) & 1, lv);
        TSW(8);
        float acc0[4] = {0.f, 0.f, 0.f, 0.f}, acc1[4] = {0.f, 0.f, 0.f, 0.f};
        const int krow = (lane & 7) + ((lane >> 4) << 3);
        const uint32_t wb = sbase + slot * SLOT_BYTES + krow * 128 + ((((wl << 1) + ((lane >> 3) & 1)) ^ (krow & 7)) << 4);
#pragma unroll
        for (int kp = 0; kp < 4; kp++) {
            uint32_t b[4], a[4], a2[4];
            ldsm4(b, s_of + brow * 272 + (kp * 32 + bch * 8) * 2);
            ldsm4t(a, wb + kp * 4096);
            ldsm4t(a2, wb + kp * 4096 + 2048);
            mma16816(acc0, a, b[0], b[1]);
            mma16816(acc1, a2, b[2], b[3]);
        }
        st_tag2(p_in1, acc0[0] + acc1[0], acc0[1] + acc1[1], tag, pw);
        st_tag2(p_in1 + 32 * 16, acc0[2] + acc1[2], acc0[3] + acc1[3], tag, pw);
        TSW(9);
    }

    float h_res = 0.f;
    if (warp == 7 || !lv) {
        const float kk = inbox_reduce<4>(q_in1, tag, lv, lane);
        TSW(20);
        h_res = bf16r(x_res + bf16r(kk));
#pragma unroll
        for (int rp = 0; rp < HREP / 2; rp++) st_tag1(p_h + rp * (NB * DM), h_res, tag, lv);
        TSW(10);
    }

    if (c < NFCTA) {
        if (warp < NB) {
            uint4 u[4];
            poll4<4>(u, q_h, tag, lv);
            TSW(21);
            float v[16];
#pragma unroll
            for (int k = 0; k < 4; k++) {
                v[4 * k + 0] = u2f(u[k].x & 0xffff0000u); v[4 * k + 1] = u2f(u[k].y & 0xffff0000u);
                v[4 * k + 2] = u2f(u[k].z & 0xffff0000u); v[4 * k + 3] = u2f(u[k].w & 0xffff0000u);
            }
            warp_layernorm_store(v, __shfl_sync(0xffffffffu, v[0], 0), s_xn + warp * 1040 + lane * 8, lv);
        }
        cons_sync_p(lv);
        TSW(11);
        {
            const int slot = (ITEM_GU + wg) % NSLOT;
            mbar_wait_p(bar_full + 8 * slot, ((ITEM_GU + wg) / NSLOT) & 1, lv);
            TSW(15);
            float ag[4] = {0.f, 0.f, 0.f, 0.f}, au[4] = {0.f, 0.f, 0.f, 0.f};
            const int krow = wl * 64 + (lane & 7) + ((lane >> 4) << 3);
            const uint32_t gb = sbase + slot * SLOT_BYTES + krow * 32 + ((((lane >> 3) & 1) ^ ((krow >> 2) & 1)) << 4);
#pragma unroll
            for (int kp = 0; kp < 2; kp++) {
                uint32_t b[4], a[4], a2[4];
                ldsm4(b, s_xn + brow * 1040 + (warp * 64 + kp * 32 + bch * 8) * 2);
                ldsm4t(a, gb + kp * 1024);
                ldsm4t(a2, gb + 8192 + kp * 1024);
                mma16816(ag, a, b[0], b[1]);
                mma16816(au, a2, b[0], b[1]);
                ldsm4t(a, gb + kp * 1024 + 512);
                ldsm4t(a2, gb + 8192 + kp * 1024 + 512);
                mma16816(ag, a, b[2], b[3]);
                mma16816(au, a2, b[2], b[3]);
            }
            const uint32_t dst = s_red + (warp * 160 + (2 * t4) * 20 + r) * 4;
            sts32(dst, ag[0], pw);        sts32(dst + 80, ag[1], pw);
            sts32(dst + 32, ag[2], pw);   sts32(dst + 80 + 32, ag[3], pw);
            sts32(dst + 320, au[0], pw);      sts32(dst + 320 + 80, au[1], pw);
            sts32(dst + 320 + 32, au[2], pw); sts32(dst + 320 + 80 + 32, au[3], pw);
            TSW(22);
            cons_sync_p(lv);
            if (vtid < 64) {
                const int b = vtid >> 4, n = vtid & 15;
                float g = 0.f, u = 0.f;
#pragma unroll
                for (int w = 0; w < 8; w++) {
                    g += lds32(s_red + (w * 160 + b * 20 + n) * 4);
                    u += lds32(s_red + (w * 160 + 80 + b * 20 + n) * 4);
                }
                g = bf16r(g); u = bf16r(u);
                const float inner = 0.7978845608028654f * (g + 0.044715f * g * g * g);
                const float ge = bf16r(__fdividef(g, 1.f + __expf(-2.f * inner)));
                sts16(s_act + (b * 24 + n) * 2, __bfloat16_as_ushort(__float2bfloat16_rn(ge * u)), lv);
            }
            cons_sync_p(lv);
        }
        {
            TSW(16);
            const int slot = (ITEM_WD + wg) % NSLOT;
            mbar_wait_p(bar_full + 8 * slot, ((ITEM_WD + wg) / NSLOT) & 1, lv);
            TSW(17);
            uint32_t b[4];
            ldsm4(b, s_act + brow * 48 + (bch & 1) * 16);
            const int krow = (lane & 7) + ((lane >> 4) << 3);
            const uint32_t db = sbase + slot * SLOT_BYTES + wl * 2048 + krow * 128;
#pragma unroll
            for (int j = 0; j < 4; j++) {
                const int chunk = 2 * j + ((lane >> 3) & 1);
                uint32_t a[4];
                ldsm4t(a, db + ((chunk ^ (krow & 7)) << 4));
                float acc[4] = {0.f, 0.f, 0.f, 0.f};
                mma16816(acc, a, b[0], b[1]);
                st_tag2(p_in2 + (2 * j) * NFCTA * 16, acc[0], acc[1], tag, pw);
                st_tag2(p_in2 + (2 * j + 1) * NFCTA * 16, acc[2], acc[3], tag, pw);
            }
            TSW(12);
        }
    }

    if (warp == 7 || !lv) {
        const float kk = inbox_reduce<14>(q_in2, tag, lv, lane);
        TSW(23);
        if (lv && !(lane & 4)) *p_out = __float2bfloat16_rn(h_res + bf16r(kk));
        if (lv && c == 0 && lane == 0) {
            const unsigned e = ld_rlx1(&g_epoch);
            asm volatile("st.relaxed.gpu.global.u32 [%0], %1;" ::"l"(&g_epoch), "r"(e + 1) : "memory");
        }
        TSW(13);
    }
}

typedef CUresult (*EncodeFn)(CUtensorMap*, CUtensorMapDataType, cuuint32_t, void*, const cuuint64_t*, const cuuint64_t*,
                             const cuuint32_t*, const cuuint32_t*, CUtensorMapInterleave, CUtensorMapSwizzle,
                             CUtensorMapL2promotion, CUtensorMapFloatOOBfill);

CUtensorMap make_map(EncodeFn enc, const void* base, int rank, const cuuint64_t* dims, const cuuint64_t* strides,
                     const cuuint32_t* box, CUtensorMapSwizzle sw, CUtensorMapL2promotion promo) {
    CUtensorMap tm;
    cuuint32_t es[3] = {1, 1, 1};
    enc(&tm, CU_TENSOR_MAP_DATA_TYPE_BFLOAT16, rank, const_cast<void*>(base), dims, strides, box, es,
        CU_TENSOR_MAP_INTERLEAVE_NONE, sw, promo, CU_TENSOR_MAP_FLOAT_OOB_FILL_NONE);
    return tm;
}

}

extern "C" void kernel_launch(void* const* d_in, const int* in_sizes, int n_in, void* d_out, int out_size) {
    (void)in_sizes; (void)n_in; (void)out_size;
    const void* x = d_in[0];
    const void* kc = d_in[1];
    const void* vc = d_in[2];
    const void* wq = d_in[3];
    const void* wo = d_in[4];
    const void* wg = d_in[6];
    const void* wu = d_in[7];
    const void* wd = d_in[8];

    static EncodeFn enc = nullptr;
    if (!enc) {
        void* fn = nullptr;
        cudaDriverEntryPointQueryResult qr;
        cudaGetDriverEntryPoint("cuTensorMapEncodeTiled", &fn, cudaEnableDefault, &qr);
        enc = reinterpret_cast<EncodeFn>(fn);
        cudaFuncSetAttribute(fused_decode_kernel, cudaFuncAttributeMaxDynamicSharedMemorySize, SMEM_BYTES);
    }
    const auto P256 = CU_TENSOR_MAP_L2_PROMOTION_L2_256B;
    CUtensorMap tmK, tmV, tmWq, tmWo, tmWg, tmWu, tmWd;
    {
        cuuint64_t dims[3] = {64, (cuuint64_t)NB * HKV * SK, 2};
        cuuint64_t str[2] = {256, 128};
        cuuint32_t box[3] = {64, 64, 2};
        tmK = make_map(enc, kc, 3, dims, str, box, CU_TENSOR_MAP_SWIZZLE_128B, P256);
        tmV = make_map(enc, vc, 3, dims, str, box, CU_TENSOR_MAP_SWIZZLE_128B, P256);
    }
    {
        cuuint64_t dims[2] = {HQ * DH, DM};
        cuuint64_t str[1] = {HQ * DH * 2};
        cuuint32_t box[2] = {32, 256};
        tmWq = make_map(enc, wq, 2, dims, str, box, CU_TENSOR_MAP_SWIZZLE_64B, P256);
    }
    {
        cuuint64_t dims[3] = {64, HQ * DH, 8};
        cuuint64_t str[2] = {DM * 2, 128};
        cuuint32_t box[3] = {64, 128, 1};
        tmWo = make_map(enc, wo, 3, dims, str, box, CU_TENSOR_MAP_SWIZZLE_128B, P256);
    }
    {
        cuuint64_t dims[2] = {FF, DM};
        cuuint64_t str[1] = {FF * 2};
        cuuint32_t box[2] = {16, 256};
        tmWg = make_map(enc, wg, 2, dims, str, box, CU_TENSOR_MAP_SWIZZLE_32B, P256);
        tmWu = make_map(enc, wu, 2, dims, str, box, CU_TENSOR_MAP_SWIZZLE_32B, P256);
    }
    {
        cuuint64_t dims[3] = {64, FF, 8};
        cuuint64_t str[2] = {DM * 2, 128};
        cuuint32_t box[3] = {64, 16, 4};
        tmWd = make_map(enc, wd, 3, dims, str, box, CU_TENSOR_MAP_SWIZZLE_128B, P256);
    }
    fused_decode_kernel<<<NCTA, NTHREADS, SMEM_BYTES, cudaStreamPerThread>>>(
        tmK, tmV, tmWq, tmWo, tmWg, tmWu, tmWd, (const __nv_bfloat16*)x, (__nv_bfloat16*)d_out);
}
```

```cpp
#include <cuda_runtime.h>
#include <cuda_bf16.h>
#include <cuda.h>
#include <stdint.h>

namespace {

constexpr int NB = 4, DM = 512, HQ = 32, HKV = 8, SK = 8192, DH = 128, FF = 1792;
constexpr int NCTA = 128;
constexpr int NSPLIT = 4;
constexpr int TILE = 128;
constexpr int NTILE = SK / NSPLIT / TILE;
constexpr int SLOT_BYTES = 16384;
constexpr int NSLOT = 12;
constexpr int ITEM_WO = 2 + 4 * NTILE;
constexpr int ITEM_GU = ITEM_WO + 2;
constexpr int ITEM_WD = ITEM_WO + 4;
constexpr int NFCTA = FF / 16;
constexpr int HREP = 4;
constexpr int NCONS = 256;
constexpr int NHELP = 4;
constexpr int NTHREADS = NCONS + 32 + 32 * NHELP;
constexpr int NALL = NCONS + 32 * NHELP;

constexpr int WINDOW = 4;
constexpr int WINDOW_EG = 5;
constexpr int EG_COUNT = 8;
constexpr int WINDOW_T = 2;
constexpr int TRIGGER = 96;
constexpr int POLL_DELAY = 300;
constexpr uint32_t SPIN_LIMIT = 1u << 22;

constexpr int SM_MRG = NSLOT * SLOT_BYTES;
constexpr int SM_ML = SM_MRG + 8 * 4 * 136 * 4;
constexpr int SM_XN = SM_ML + 8 * 4 * 2 * 4;
constexpr int SM_QS = SM_XN + 4 * 520 * 2;
constexpr int SM_OF = SM_QS + 4 * 136 * 2;
constexpr int SM_ACT = SM_OF + 4 * 136 * 2;
constexpr int SM_BAR = SM_ACT + 4 * 24 * 2;
constexpr int SM_CNT = SM_BAR + 2 * NSLOT * 8;
constexpr int SM_TOTAL = SM_CNT + 16;
constexpr int SMEM_BYTES = SM_TOTAL + 1024;

__device__ unsigned g_epoch;
__device__ unsigned g_count;
__device__ __align__(128) float g_q[NB * HQ * DH];
__device__ __align__(128) float g_po[NCTA * 4 * DH];
__device__ __align__(128) float g_pml[NCTA * 4 * 2];
__device__ __align__(128) float g_in1[NCTA * 32 * 16];
__device__ __align__(128) float g_h[HREP * NB * DM];
__device__ __align__(128) float g_in2[NCTA * NFCTA * 16];

__device__ __forceinline__ uint32_t smem_u32(const void* p) { return (uint32_t)__cvta_generic_to_shared(p); }
__device__ __forceinline__ void mbar_init(uint32_t bar, uint32_t cnt) {
    asm volatile("mbarrier.init.shared::cta.b64 [%0], %1;" ::"r"(bar), "r"(cnt) : "memory");
}
__device__ __forceinline__ void mbar_expect_tx(uint32_t bar, uint32_t bytes) {
    asm volatile("mbarrier.arrive.expect_tx.shared::cta.b64 _, [%0], %1;" ::"r"(bar), "r"(bytes) : "memory");
}
__device__ __forceinline__ void mbar_arrive(uint32_t bar) {
    asm volatile("mbarrier.arrive.shared::cta.b64 _, [%0];" ::"r"(bar) : "memory");
}
__device__ __forceinline__ void mbar_wait(uint32_t bar, uint32_t parity) {
    uint32_t done = 0, it = 0;
    while (true) {
        asm volatile("{\n.reg .pred p;\nmbarrier.try_wait.parity.shared::cta.b64 p, [%1], %2;\nselp.u32 %0, 1, 0, p;\n}"
                     : "=r"(done) : "r"(bar), "r"(parity) : "memory");
        if (done) break;
        if (++it > SPIN_LIMIT) __trap();
    }
}
__device__ __forceinline__ void mbar_wait_p(uint32_t bar, uint32_t parity, uint32_t lv) {
    uint32_t it = 0;
    while (true) {
        uint32_t done;
        asm volatile("{\n.reg .pred p, q;\nsetp.ne.u32 q, %3, 0;\nsetp.eq.u32 p, %3, 0;\n"
                     "@q mbarrier.try_wait.parity.shared::cta.b64 p, [%1], %2;\nselp.u32 %0, 1, 0, p;\n}"
                     : "=r"(done) : "r"(bar), "r"(parity), "r"(lv) : "memory");
        if (done) break;
        if (++it > SPIN_LIMIT) __trap();
    }
}
__device__ __forceinline__ void tma2d(uint32_t dst, const CUtensorMap* tm, int c0, int c1, uint32_t bar, uint64_t pol) {
    asm volatile("cp.async.bulk.tensor.2d.shared::cluster.global.mbarrier::complete_tx::bytes.L2::cache_hint [%0], [%1, {%3, %4}], [%2], %5;"
                 ::"r"(dst), "l"(tm), "r"(bar), "r"(c0), "r"(c1), "l"(pol) : "memory");
}
__device__ __forceinline__ void tma3d(uint32_t dst, const CUtensorMap* tm, int c0, int c1, int c2, uint32_t bar, uint64_t pol) {
    asm volatile("cp.async.bulk.tensor.3d.shared::cluster.global.mbarrier::complete_tx::bytes.L2::cache_hint [%0], [%1, {%3, %4, %5}], [%2], %6;"
                 ::"r"(dst), "l"(tm), "r"(bar), "r"(c0), "r"(c1), "r"(c2), "l"(pol) : "memory");
}
__device__ __forceinline__ void tm_prefetch(const CUtensorMap* tm) {
    asm volatile("prefetch.tensormap [%0];" ::"l"(tm) : "memory");
}
__device__ __forceinline__ void ldsm4(uint32_t (&r)[4], uint32_t addr) {
    asm volatile("ldmatrix.sync.aligned.m8n8.x4.shared.b16 {%0,%1,%2,%3}, [%4];"
                 : "=r"(r[0]), "=r"(r[1]), "=r"(r[2]), "=r"(r[3]) : "r"(addr) : "memory");
}
__device__ __forceinline__ void ldsm4t(uint32_t (&r)[4], uint32_t addr) {
    asm volatile("ldmatrix.sync.aligned.m8n8.x4.trans.shared.b16 {%0,%1,%2,%3}, [%4];"
                 : "=r"(r[0]), "=r"(r[1]), "=r"(r[2]), "=r"(r[3]) : "r"(addr) : "memory");
}
__device__ __forceinline__ void mma16816(float (&c)[4], const uint32_t (&a)[4], uint32_t b0, uint32_t b1) {
    asm volatile("mma.sync.aligned.m16n8k16.row.col.f32.bf16.bf16.f32 {%0,%1,%2,%3}, {%4,%5,%6,%7}, {%8,%9}, {%0,%1,%2,%3};"
                 : "+f"(c[0]), "+f"(c[1]), "+f"(c[2]), "+f"(c[3])
                 : "r"(a[0]), "r"(a[1]), "r"(a[2]), "r"(a[3]), "r"(b0), "r"(b1));
}
__device__ __forceinline__ uint32_t movm_t(uint32_t a) {
    uint32_t d;
    asm volatile("movmatrix.sync.aligned.m8n8.trans.b16 %0, %1;" : "=r"(d) : "r"(a));
    return d;
}
__device__ __forceinline__ uint32_t pack_bf16(float lo, float hi) {
    uint32_t d;
    asm("cvt.rn.bf16x2.f32 %0, %1, %2;" : "=r"(d) : "f"(hi), "f"(lo));
    return d;
}
__device__ __forceinline__ float bf16r(float x) { return __bfloat162float(__float2bfloat16_rn(x)); }
__device__ __forceinline__ float bf_lo(uint32_t w) { return __uint_as_float(w << 16); }
__device__ __forceinline__ float bf_hi(uint32_t w) { return __uint_as_float(w & 0xffff0000u); }
__device__ __forceinline__ float ex2(float x) {
    float y;
    asm("ex2.approx.ftz.f32 %0, %1;" : "=f"(y) : "f"(x));
    return y;
}
__device__ __forceinline__ void cons_sync() { asm volatile("bar.sync 1, 256;" ::: "memory"); }
template <int ID, int CNT> __device__ __forceinline__ void bar_sync_p(uint32_t lv) {
    asm volatile("{\n.reg .pred q;\nsetp.ne.u32 q, %0, 0;\n@q bar.sync %1, %2;\n}" ::"r"(lv), "n"(ID), "n"(CNT) : "memory");
}
template <int ID, int CNT> __device__ __forceinline__ void bar_arrive_p(uint32_t lv) {
    asm volatile("{\n.reg .pred q;\nsetp.ne.u32 q, %0, 0;\n@q bar.arrive %1, %2;\n}" ::"r"(lv), "n"(ID), "n"(CNT) : "memory");
}
__device__ __forceinline__ void spin_cycles(uint32_t n) {
    const uint32_t t0 = (uint32_t)clock();
    while ((uint32_t)clock() - t0 < n) {}
}
__device__ __forceinline__ void sts32(uint32_t a, float v, uint32_t p) {
    asm volatile("{\n.reg .pred q;\nsetp.ne.u32 q, %2, 0;\n@q st.shared.f32 [%0], %1;\n}" ::"r"(a), "f"(v), "r"(p) : "memory");
}
__device__ __forceinline__ void sts16(uint32_t a, uint16_t v, uint32_t p) {
    asm volatile("{\n.reg .pred q;\nsetp.ne.u32 q, %2, 0;\n@q st.shared.u16 [%0], %1;\n}" ::"r"(a), "h"(v), "r"(p) : "memory");
}
__device__ __forceinline__ void sts64(uint32_t a, uint32_t x, uint32_t y, uint32_t p) {
    asm volatile("{\n.reg .pred q;\nsetp.ne.u32 q, %3, 0;\n@q st.shared.v2.u32 [%0], {%1, %2};\n}" ::"r"(a), "r"(x), "r"(y), "r"(p) : "memory");
}
__device__ __forceinline__ float lds32(uint32_t a) {
    float v; asm volatile("ld.shared.f32 %0, [%1];" : "=f"(v) : "r"(a) : "memory"); return v;
}
__device__ __forceinline__ float2 lds64(uint32_t a) {
    float2 v; asm volatile("ld.shared.v2.f32 {%0, %1}, [%2];" : "=f"(v.x), "=f"(v.y) : "r"(a) : "memory"); return v;
}

__device__ __forceinline__ float u2f(uint32_t u) { return __uint_as_float(u); }
__device__ __forceinline__ float tagf(float v, uint32_t tag) { return __uint_as_float((__float_as_uint(v) & ~1u) | tag); }
__device__ __forceinline__ void st_tag1(float* ptr, float v, uint32_t tag, uint32_t p) {
    asm volatile("{\n.reg .pred q;\nsetp.ne.u32 q, %2, 0;\n@q st.relaxed.gpu.global.f32 [%0], %1;\n}"
                 ::"l"(ptr), "f"(tagf(v, tag)), "r"(p) : "memory");
}
__device__ __forceinline__ void st_tag2(float* ptr, float a, float b, uint32_t tag, uint32_t p) {
    asm volatile("{\n.reg .pred q;\nsetp.ne.u32 q, %3, 0;\n@q st.relaxed.gpu.global.v2.f32 [%0], {%1, %2};\n}"
                 ::"l"(ptr), "f"(tagf(a, tag)), "f"(tagf(b, tag)), "r"(p) : "memory");
}
__device__ __forceinline__ void ld_rlx4(uint4& v, const float* ptr, uint32_t p) {
    asm volatile("{\n.reg .pred q;\nsetp.ne.u32 q, %5, 0;\n@q ld.relaxed.gpu.global.v4.u32 {%0,%1,%2,%3}, [%4];\n}"
                 : "+r"(v.x), "+r"(v.y), "+r"(v.z), "+r"(v.w) : "l"(ptr), "r"(p) : "memory");
}
__device__ __forceinline__ void ld_rlx2(uint2& v, const float* ptr, uint32_t p) {
    asm volatile("{\n.reg .pred q;\nsetp.ne.u32 q, %3, 0;\n@q ld.relaxed.gpu.global.v2.u32 {%0,%1}, [%2];\n}"
                 : "+r"(v.x), "+r"(v.y) : "l"(ptr), "r"(p) : "memory");
}
__device__ __forceinline__ uint32_t ld_rlx1(const unsigned* p) {
    uint32_t v;
    asm volatile("ld.relaxed.gpu.global.u32 %0, [%1];" : "=r"(v) : "l"(p) : "memory");
    return v;
}
__device__ __forceinline__ uint32_t bad4(const uint4& v, uint32_t tag) {
    uint32_t u, w, r;
    asm("lop3.b32 %0, %1, %2, %3, 0x7E;" : "=r"(u) : "r"(v.x), "r"(v.y), "r"(tag));
    asm("lop3.b32 %0, %1, %2, %3, 0x7E;" : "=r"(w) : "r"(v.z), "r"(v.w), "r"(tag));
    asm("lop3.b32 %0, %1, %2, 1, 0xA8;" : "=r"(r) : "r"(u), "r"(w));
    return r;
}
__device__ __forceinline__ uint32_t bad2(const uint2& v, uint32_t tag) {
    uint32_t u;
    asm("lop3.b32 %0, %1, %2, %3, 0x7E;" : "=r"(u) : "r"(v.x), "r"(v.y), "r"(tag));
    return u & 1u;
}
template <typename T> __device__ __forceinline__ void pin(T*& p) { asm volatile("" : "+l"(p)); }
__device__ __forceinline__ void pin(uint32_t& v) { asm volatile("" : "+r"(v)); }
__device__ __forceinline__ float sqrt_approx(float x) { float y; asm("sqrt.approx.ftz.f32 %0, %1;" : "=f"(y) : "f"(x)); return y; }
__device__ __forceinline__ float rcp_approx(float x) { float y; asm("rcp.approx.ftz.f32 %0, %1;" : "=f"(y) : "f"(x)); return y; }
template <int NK, int KS, int NM, int MS>
struct PollSet {
    uint4 v[NK]; uint2 m[NM > 0 ? NM : 1]; uint32_t bad[NK], badm[NM > 0 ? NM : 1];
    __device__ __forceinline__ void init(uint32_t tag, uint32_t lv) {
#pragma unroll
        for (int k = 0; k < NK; k++) { v[k] = make_uint4(tag, tag, tag, tag); bad[k] = lv; }
#pragma unroll
        for (int k = 0; k < NM; k++) { m[k] = make_uint2(tag, tag); badm[k] = lv; }
    }
    __device__ __forceinline__ void issue(const float* src, const float* src2) {
#pragma unroll
        for (int k = 0; k < NK; k++) ld_rlx4(v[k], src + k * KS, bad[k]);
#pragma unroll
        for (int k = 0; k < NM; k++) ld_rlx2(m[k], src2 + k * MS, badm[k]);
    }
    __device__ __forceinline__ bool complete(uint32_t tag) {
        uint32_t any = 0;
#pragma unroll
        for (int k = 0; k < NK; k++) { bad[k] = bad4(v[k], tag); any |= bad[k]; }
#pragma unroll
        for (int k = 0; k < NM; k++) { badm[k] = bad2(m[k], tag); any |= badm[k]; }
        return !__any_sync(0xffffffffu, any);
    }
};
constexpr float LOG2E = 1.4426950408889634f;

__device__ __forceinline__ void warp_layernorm_store(const float (&v)[16], float c, uint32_t dst, uint32_t p) {
    float s1[4], s2[4];
#pragma unroll
    for (int k = 0; k < 4; k++) {
        const float d0 = v[4 * k] - c, d1 = v[4 * k + 1] - c, d2 = v[4 * k + 2] - c, d3 = v[4 * k + 3] - c;
        s1[k] = (d0 + d1) + (d2 + d3);
        s2[k] = fmaf(d0, d0, d1 * d1) + fmaf(d2, d2, d3 * d3);
    }
    float t1 = (s1[0] + s1[1]) + (s1[2] + s1[3]), t2 = (s2[0] + s2[1]) + (s2[2] + s2[3]);
#pragma unroll
    for (int o = 16; o > 0; o >>= 1) {
        t1 += __shfl_xor_sync(0xffffffffu, t1, o);
        t2 += __shfl_xor_sync(0xffffffffu, t2, o);
    }
    const float md = t1 * (1.f / 512.f);
    const float mean = bf16r(c + md);
    const float var = bf16r(fmaxf(fmaf(-md, md, t2 * (1.f / 512.f)), 0.f));
    const float inv = rcp_approx(bf16r(sqrt_approx(bf16r(var + 1e-5f))));
#pragma unroll
    for (int k = 0; k < 4; k++) {
        const uint32_t t01 = pack_bf16(v[4 * k + 0] - mean, v[4 * k + 1] - mean);
        const uint32_t t23 = pack_bf16(v[4 * k + 2] - mean, v[4 * k + 3] - mean);
        sts64(dst + k * 256, pack_bf16(bf_lo(t01) * inv, bf_hi(t01) * inv), pack_bf16(bf_lo(t23) * inv, bf_hi(t23) * inv), p);
    }
}

template <class PS>
__device__ __forceinline__ void poll1(PS& ps, const float* src, const float* src2, uint32_t tag, uint32_t lv) {
    ps.init(tag, lv);
    uint32_t it = 0;
    while (true) {
        ps.issue(src, src2);
        if (ps.complete(tag)) break;
        if (++it > SPIN_LIMIT) __trap();
    }
}
template <int NK>
__device__ __forceinline__ float inbox_reduce(const float* src, uint32_t tag, uint32_t lv, int lane) {
    PollSet<NK, 128, 0, 0> ps;
    poll1(ps, src, src, tag, lv);
    float a = 0.f, b = 0.f, c = 0.f, d = 0.f, a2 = 0.f, b2 = 0.f, c2 = 0.f, d2 = 0.f;
#pragma unroll
    for (int k = 0; k < NK; k += 2) {
        a += u2f(ps.v[k].x); b += u2f(ps.v[k].y); c += u2f(ps.v[k].z); d += u2f(ps.v[k].w);
        a2 += u2f(ps.v[k + 1].x); b2 += u2f(ps.v[k + 1].y); c2 += u2f(ps.v[k + 1].z); d2 += u2f(ps.v[k + 1].w);
    }
    a += a2; b += b2; c += c2; d += d2;
    const bool hi = lane & 16, h2 = lane & 8;
    float k0 = hi ? c : a, k1 = hi ? d : b;
    k0 += __shfl_xor_sync(0xffffffffu, hi ? a : c, 16);
    k1 += __shfl_xor_sync(0xffffffffu, hi ? b : d, 16);
    float kk = h2 ? k1 : k0;
    kk += __shfl_xor_sync(0xffffffffu, h2 ? k0 : k1, 8);
    kk += __shfl_xor_sync(0xffffffffu, kk, 4);
    return kk;
}


__global__ void __launch_bounds__(NTHREADS, 1)
fused_decode_kernel(const __grid_constant__ CUtensorMap tmK, const __grid_constant__ CUtensorMap tmV,
                    const __grid_constant__ CUtensorMap tmWq, const __grid_constant__ CUtensorMap tmWo,
                    const __grid_constant__ CUtensorMap tmWg, const __grid_constant__ CUtensorMap tmWu,
                    const __grid_constant__ CUtensorMap tmWd,
                    const __nv_bfloat16* __restrict__ x, __nv_bfloat16* __restrict__ out) {
    extern __shared__ uint8_t smem_raw[];
    const uint32_t sbase = (smem_u32(smem_raw) + 1023u) & ~1023u;
    const uint32_t bar_full = sbase + SM_BAR, bar_empty = bar_full + NSLOT * 8;
    const int tid = threadIdx.x, lane = tid & 31;
    const int c = blockIdx.x;
    const int row0 = (c >> 2) * SK + (c & 3) * (SK / NSPLIT);
    uint64_t pol_stream = 0;
    if (tid == NCONS) {
        tm_prefetch(&tmWq); tm_prefetch(&tmK); tm_prefetch(&tmV);
        for (int i = 0; i < 4; i++) mbar_init(bar_full + 8 * i, 1);
        asm volatile("fence.proxy.async.shared::cta;" ::: "memory");
        asm volatile("createpolicy.fractional.L2::evict_first.b64 %0, 1.0;" : "=l"(pol_stream));
        mbar_expect_tx(bar_full, SLOT_BYTES);
        tma2d(sbase, &tmWq, 32 * c, 0, bar_full, pol_stream);
        mbar_expect_tx(bar_full + 16, SLOT_BYTES);
        tma3d(sbase + 2 * SLOT_BYTES, &tmK, 0, row0, 0, bar_full + 16, pol_stream);
        mbar_expect_tx(bar_full + 8, SLOT_BYTES);
        tma2d(sbase + SLOT_BYTES, &tmWq, 32 * c, 256, bar_full + 8, pol_stream);
        mbar_expect_tx(bar_full + 24, SLOT_BYTES);
        tma3d(sbase + 3 * SLOT_BYTES, &tmK, 0, row0 + 64, 0, bar_full + 24, pol_stream);
        for (int i = 4; i < NSLOT; i++) mbar_init(bar_full + 8 * i, 1);
        for (int i = 0; i < NSLOT; i++) mbar_init(bar_empty + 8 * i, 4);
        asm volatile("fence.proxy.async.shared::cta;" ::: "memory");
        asm volatile("st.volatile.shared.u32 [%0], %1;" ::"r"(sbase + SM_CNT), "r"(0) : "memory");
    }
    __syncthreads();

    if ((tid >> 5) == 8) {
        if (lane == 0) {
            auto acquire = [&](int i, int window) {
                if (i >= NSLOT) mbar_wait(bar_empty + 8 * (i % NSLOT), ((i / NSLOT) - 1) & 1);
                if (i >= window) { const int j = i - window; mbar_wait(bar_full + 8 * (j % NSLOT), (j / NSLOT) & 1); }
            };
            auto seen_count = [&]() {
                uint32_t seen;
                asm volatile("ld.volatile.shared.u32 %0, [%1];" : "=r"(seen) : "r"(sbase + SM_CNT) : "memory");
                return (int)seen;
            };
#pragma unroll 1
            for (int i = 4; i < ITEM_WO; i++) {
                const int slot = i % NSLOT;
                acquire(i, (i >= ITEM_WO - 24 && seen_count() >= EG_COUNT) ? WINDOW_EG : WINDOW);
                const int t = (i - 2) >> 2, sub = (i - 2) & 3;
                mbar_expect_tx(bar_full + 8 * slot, SLOT_BYTES);
                tma3d(sbase + slot * SLOT_BYTES, (sub & 2) ? &tmV : &tmK, 0, row0 + t * TILE + (sub & 1) * 64, 0,
                      bar_full + 8 * slot, pol_stream);
            }
            asm volatile("red.relaxed.gpu.global.add.u32 [%0], 1;" ::"l"(&g_count) : "memory");
            {
                uint32_t it = 0;
                while (seen_count() < TRIGGER) {
                    __nanosleep(20);
                    if (++it > SPIN_LIMIT) __trap();
                }
            }
#pragma unroll 1
            for (int hf = 0; hf < 2; hf++) {
                const int i = ITEM_WO + hf, slot = i % NSLOT;
                acquire(i, WINDOW_T);
                mbar_expect_tx(bar_full + 8 * slot, SLOT_BYTES);
                tma3d(sbase + slot * SLOT_BYTES, &tmWo, 0, 128 * (c >> 2), 2 * (c & 3) + hf, bar_full + 8 * slot, pol_stream);
            }
            if (c < NFCTA) {
#pragma unroll 1
                for (int hf = 0; hf < 2; hf++) {
                    const int i = ITEM_GU + hf, slot = i % NSLOT;
                    acquire(i, WINDOW_T);
                    const uint32_t fb = bar_full + 8 * slot, dst = sbase + slot * SLOT_BYTES;
                    mbar_expect_tx(fb, SLOT_BYTES);
                    tma2d(dst, &tmWg, 16 * c, 256 * hf, fb, pol_stream);
                    tma2d(dst + 8192, &tmWu, 16 * c, 256 * hf, fb, pol_stream);
                }
#pragma unroll 1
                for (int hf = 0; hf < 2; hf++) {
                    const int i = ITEM_WD + hf, slot = i % NSLOT;
                    acquire(i, WINDOW_T);
                    mbar_expect_tx(bar_full + 8 * slot, 8192);
                    tma3d(sbase + slot * SLOT_BYTES, &tmWd, 0, 16 * c, 4 * hf, bar_full + 8 * slot, pol_stream);
                }
            }
        }
        return;
    }

    uint32_t lv;
    asm volatile("mov.u32 %0, %1;" : "=r"(lv) : "r"((tid < NCONS) ? 1u : 0u));
    const int warp = lv ? (tid >> 5) : 0;
    const int vtid = warp * 32 + lane;
    const int r = lane >> 2, t4 = lane & 3;
    const int wg = warp >> 2, wl = warp & 3;
    const uint32_t s_red = sbase + SM_MRG, s_ml = sbase + SM_ML, s_xn = sbase + SM_XN;
    const uint32_t s_qs = sbase + SM_QS, s_of = sbase + SM_OF, s_act = sbase + SM_ACT;
    const int brow = lane & 3, bch = lane >> 3;

    const unsigned epoch = ld_rlx1(&g_epoch);
    const uint32_t tag = (epoch & 1u) ^ 1u;

    float* p_po = &g_po[(c * 4 + (vtid >> 6)) * DH + (vtid & 63) * 2];
    float* p_pml = &g_pml[(c * 4 + (vtid >> 6)) * 2];
    float* p_in1 = &g_in1[((t4 * 64 + 16 * (c & 3) + 2 * warp) * 32 + (c >> 2)) * 16 + 2 * r];
    float* p_in2 = &g_in2[((t4 * 64 + 8 * warp) * NFCTA + (c < NFCTA ? c : 0)) * 16 + 2 * r];
    pin(p_po); pin(p_pml); pin(p_in1); pin(p_in2);

    float o[8][4];
#pragma unroll
    for (int j = 0; j < 8; j++) { o[j][0] = o[j][1] = o[j][2] = o[j][3] = 0.f; }
    float mfin0 = 0.f, mfin1 = 0.f;

    if (lv) {
        if (warp < NB) {
            float v[16];
#pragma unroll
            for (int k = 0; k < 4; k++) {
                uint2 w = *reinterpret_cast<const uint2*>(x + warp * DM + k * 128 + lane * 4);
                v[4 * k + 0] = bf_lo(w.x); v[4 * k + 1] = bf_hi(w.x); v[4 * k + 2] = bf_lo(w.y); v[4 * k + 3] = bf_hi(w.y);
            }
            warp_layernorm_store(v, __shfl_sync(0xffffffffu, v[0], 0), s_xn + warp * 1040 + lane * 8, 1u);
        }
        cons_sync();

        mbar_wait(bar_full + 8 * wg, 0);
        {
            float acc[2][4] = {};
#pragma unroll
            for (int kp = 0; kp < 2; kp++) {
                uint32_t b[4];
                ldsm4(b, s_xn + brow * 1040 + (warp * 64 + kp * 32 + bch * 8) * 2);
#pragma unroll
                for (int k2 = 0; k2 < 2; k2++) {
                    const int krow = warp * 64 + kp * 32 + k2 * 16 + (lane & 7) + ((lane >> 4) << 3);
#pragma unroll
                    for (int mt = 0; mt < 2; mt++) {
                        const int chunk = mt * 2 + ((lane >> 3) & 1);
                        uint32_t a[4];
                        ldsm4t(a, sbase + krow * 64 + ((chunk ^ ((krow >> 1) & 3)) << 4));
                        mma16816(acc[mt], a, b[2 * k2], b[2 * k2 + 1]);
                    }
                }
            }
            __syncwarp();
            if (lane == 0) mbar_arrive(bar_empty + 8 * wg);
            const uint32_t pq = t4 < 2;
#pragma unroll
            for (int mt = 0; mt < 2; mt++) {
                const uint32_t dst = s_red + (warp * 144 + (2 * t4) * 36 + mt * 16 + r) * 4;
                sts32(dst, acc[mt][0], pq); sts32(dst + 144, acc[mt][1], pq);
                sts32(dst + 32, acc[mt][2], pq); sts32(dst + 144 + 32, acc[mt][3], pq);
            }
            cons_sync();
            if (tid < 128) {
                float s = 0.f;
#pragma unroll
                for (int w = 0; w < 8; w++) s += lds32(s_red + (w * 144 + warp * 36 + lane) * 4);
                st_tag1(&g_q[warp * (HQ * DH) + 32 * c + lane], bf16r(s), tag, 1u);
                const int g = c >> 2;
                const float* src = &g_q[(g >> 3) * (HQ * DH) + (g & 7) * 512 + tid * 4];
                uint4 v;
                uint32_t it = 0;
                while (true) {
                    ld_rlx4(v, src, 1u);
                    if (!(bad4(v, tag) & 1)) break;
                    if (++it > SPIN_LIMIT) __trap();
                }
                sts64(s_qs + (warp * 136 + lane * 4) * 2, (v.x >> 16) | (v.y & 0xffff0000u), (v.z >> 16) | (v.w & 0xffff0000u), 1u);
            }
            cons_sync();
        }

        uint32_t qf[8][2];
#pragma unroll
        for (int j = 0; j < 8; j += 2) {
            uint32_t b[4];
            ldsm4(b, s_qs + brow * 272 + (j * 16 + bch * 8) * 2);
            qf[j][0] = b[0]; qf[j][1] = b[1]; qf[j + 1][0] = b[2]; qf[j + 1][1] = b[3];
        }
        const int krow = wl * 16 + (lane & 7) + (((lane >> 3) & 1) << 3);
        const int kch = lane >> 4;
        const int vrow = wl * 16 + (lane & 7) + ((lane >> 4) << 3);
        const int vch = (lane >> 3) & 1;
        const float scale = 0.08838834764831845f;
        float m0 = -INFINITY, m1 = -INFINITY, l0 = 0.f, l1 = 0.f;

#pragma unroll 1
        for (int t = 0; t < NTILE; t++) {
            const int ik = 2 + 4 * t + wg, iv = ik + 2;
            const int sk = ik % NSLOT, sv = iv % NSLOT;
            mbar_wait(bar_full + 8 * sk, (ik / NSLOT) & 1);
            float sa[4] = {0.f, 0.f, 0.f, 0.f}, sb[4] = {0.f, 0.f, 0.f, 0.f};
            const uint32_t kb = sbase + sk * SLOT_BYTES + krow * 128;
#pragma unroll
            for (int j = 0; j < 8; j += 2) {
                uint32_t a0[4], a1[4];
                ldsm4(a0, kb + (j >> 2) * 8192 + (((((j & 3) << 1) + kch) ^ (krow & 7)) << 4));
                ldsm4(a1, kb + ((j + 1) >> 2) * 8192 + ((((((j + 1) & 3) << 1) + kch) ^ (krow & 7)) << 4));
                mma16816(sa, a0, qf[j][0], qf[j][1]);
                mma16816(sb, a1, qf[j + 1][0], qf[j + 1][1]);
            }
            __syncwarp();
            if (lane == 0) mbar_arrive(bar_empty + 8 * sk);
            const float s0 = bf16r(bf16r(sa[0] + sb[0]) * scale), s1 = bf16r(bf16r(sa[1] + sb[1]) * scale);
            const float s2 = bf16r(bf16r(sa[2] + sb[2]) * scale), s3 = bf16r(bf16r(sa[3] + sb[3]) * scale);
            float x0 = fmaxf(fmaxf(s0, s2), m0), x1 = fmaxf(fmaxf(s1, s3), m1);
#pragma unroll
            for (int off = 4; off < 32; off <<= 1) {
                x0 = fmaxf(x0, __shfl_xor_sync(0xffffffffu, x0, off));
                x1 = fmaxf(x1, __shfl_xor_sync(0xffffffffu, x1, off));
            }
            if (t == NTILE - 1) {
                if (r == 0 && t4 < 2) asm volatile("st.shared.v2.f32 [%0], {%1, %2};" ::"r"(s_ml + (warp * 4 + t4 * 2) * 4), "f"(x0), "f"(x1) : "memory");
                cons_sync();
#pragma unroll
                for (int w = 0; w < 8; w++) {
                    const float2 mw = lds64(s_ml + (w * 4 + (t4 & 1) * 2) * 4);
                    x0 = fmaxf(x0, mw.x); x1 = fmaxf(x1, mw.y);
                }
            }
            if (__any_sync(0xffffffffu, (x0 > m0) || (x1 > m1))) {
                const float a0 = ex2((m0 - x0) * LOG2E), a1 = ex2((m1 - x1) * LOG2E);
                m0 = x0; m1 = x1;
                l0 *= a0; l1 *= a1;
#pragma unroll
                for (int j = 0; j < 8; j++) { o[j][0] *= a0; o[j][1] *= a1; o[j][2] *= a0; o[j][3] *= a1; }
            }
            const float p0 = ex2((s0 - m0) * LOG2E), p1 = ex2((s1 - m1) * LOG2E);
            const float p2 = ex2((s2 - m0) * LOG2E), p3 = ex2((s3 - m1) * LOG2E);
            l0 += p0 + p2; l1 += p1 + p3;
            const uint32_t pb0 = movm_t(pack_bf16(p0, p1));
            const uint32_t pb1 = movm_t(pack_bf16(p2, p3));
            if (t == NTILE - 1) {
#pragma unroll
                for (int off = 4; off < 32; off <<= 1) {
                    l0 += __shfl_xor_sync(0xffffffffu, l0, off);
                    l1 += __shfl_xor_sync(0xffffffffu, l1, off);
                }
                if (r == 0 && t4 < 2) asm volatile("st.shared.v2.f32 [%0], {%1, %2};" ::"r"(s_ml + 128 + (warp * 4 + t4 * 2) * 4), "f"(l0), "f"(l1) : "memory");
            }

            mbar_wait(bar_full + 8 * sv, (iv / NSLOT) & 1);
            const uint32_t vb = sbase + sv * SLOT_BYTES + vrow * 128;
#pragma unroll
            for (int j = 0; j < 8; j++) {
                uint32_t a[4];
                ldsm4t(a, vb + (j >> 2) * 8192 + (((((j & 3) << 1) + vch) ^ (vrow & 7)) << 4));
                mma16816(o[j], a, pb0, pb1);
            }
            __syncwarp();
            if (lane == 0) mbar_arrive(bar_empty + 8 * sv);
        }
        mfin0 = m0; mfin1 = m1;
    } else {
        __nanosleep(6000);
        const int wt = tid - (NCONS + 32);
        const float z = __uint_as_float(tag ^ 1u);
        auto st4 = [&](float* p) {
            asm volatile("st.relaxed.gpu.global.v4.f32 [%0], {%1, %1, %1, %1};" ::"l"(p), "f"(z) : "memory");
        };
        st4(&g_po[c * 512 + wt * 4]);
        st4(&g_in1[((((wt >> 2) >> 4) * 64 + 16 * (c & 3) + ((wt >> 2) & 15)) * 32 + (c >> 2)) * 16 + (wt & 3) * 4]);
        if (c < NFCTA)
            for (int i = wt; i < 512; i += 128) st4(&g_in2[((i >> 2) * NFCTA + c) * 16 + (i & 3) * 4]);
        if (wt < 16) st4(&g_h[(wt >> 2) * (NB * DM) + (2 * (c >> 6) + ((wt >> 1) & 1)) * DM + 8 * (c & 63) + (wt & 1) * 4]);
        else if (wt < 18) st4(&g_pml[c * 8 + (wt - 16) * 4]);
        asm volatile("bar.arrive 2, %0;" ::"n"(NALL) : "memory");
    }

    const uint32_t pw = lv && (t4 < 2);
    {
        const uint32_t dst = s_red + (warp * 544 + (2 * t4) * 136 + r) * 4;
#pragma unroll
        for (int j = 0; j < 8; j++) {
            sts32(dst + j * 64, o[j][0], pw);
            sts32(dst + 544 + j * 64, o[j][1], pw);
            sts32(dst + j * 64 + 32, o[j][2], pw);
            sts32(dst + 544 + j * 64 + 32, o[j][3], pw);
        }
        const int h = vtid >> 6;
        const uint32_t src = s_red + (h * 136 + (vtid & 63) * 2) * 4;
        const float Mh = __shfl_sync(0xffffffffu, (h & 1) ? mfin1 : mfin0, h >> 1);
        bar_sync_p<2, NALL>(lv);
        float2 ov[8]; float lw[8];
#pragma unroll
        for (int w = 0; w < 8; w++) { ov[w] = lds64(src + w * 2176); lw[w] = lds32(s_ml + 128 + (w * 4 + h) * 4); }
        const float a0 = ((ov[0].x + ov[1].x) + (ov[2].x + ov[3].x)) + ((ov[4].x + ov[5].x) + (ov[6].x + ov[7].x));
        const float a1 = ((ov[0].y + ov[1].y) + (ov[2].y + ov[3].y)) + ((ov[4].y + ov[5].y) + (ov[6].y + ov[7].y));
        const float L = ((lw[0] + lw[1]) + (lw[2] + lw[3])) + ((lw[4] + lw[5]) + (lw[6] + lw[7]));
        st_tag2(p_po, a0, a1, tag, lv);
        st_tag2(p_pml, Mh, L, tag, lv && (vtid & 63) == 0);
    }
    {
        const int slot = (ITEM_WO + wg) % NSLOT;
        mbar_wait_p(bar_full + 8 * slot, ((ITEM_WO + wg) / NSLOT) & 1, lv);
        const int krow = (lane & 7) + ((lane >> 4) << 3);
        const uint32_t wb = sbase + slot * SLOT_BYTES + krow * 128 + ((((wl << 1) + ((lane >> 3) & 1)) ^ (krow & 7)) << 4);
        uint32_t a[8][4];
#pragma unroll
        for (int ks = 0; ks < 8; ks++) ldsm4t(a[ks], wb + ks * 2048);
        uint32_t sb = s_of + brow * 272 + bch * 16;
        pin(sb);
        bar_sync_p<3, NALL>(lv);
        uint32_t b[4][4];
#pragma unroll
        for (int kp = 0; kp < 4; kp++) ldsm4(b[kp], sb + kp * 64);
        float acc[4][4] = {};
#pragma unroll
        for (int kp = 0; kp < 4; kp++) {
            mma16816(acc[kp], a[2 * kp], b[kp][0], b[kp][1]);
            mma16816(acc[kp], a[2 * kp + 1], b[kp][2], b[kp][3]);
        }
        st_tag2(p_in1, (acc[0][0] + acc[1][0]) + (acc[2][0] + acc[3][0]), (acc[0][1] + acc[1][1]) + (acc[2][1] + acc[3][1]), tag, pw);
        st_tag2(p_in1 + 32 * 16, (acc[0][2] + acc[1][2]) + (acc[2][2] + acc[3][2]), (acc[0][3] + acc[1][3]) + (acc[2][3] + acc[3][3]), tag, pw);
        bar_arrive_p<8, NCONS + 32>(lv);
    }
    if (c < NFCTA) {
        uint32_t ag[4][4], au[4][4], ad[4][4];
        {
            const int slot = (ITEM_GU + wg) % NSLOT;
            mbar_wait_p(bar_full + 8 * slot, ((ITEM_GU + wg) / NSLOT) & 1, lv);
            const int krow = wl * 64 + (lane & 7) + ((lane >> 4) << 3);
            const uint32_t gb = sbase + slot * SLOT_BYTES + krow * 32 + ((((lane >> 3) & 1) ^ ((krow >> 2) & 1)) << 4);
#pragma unroll
            for (int ks = 0; ks < 4; ks++) { ldsm4t(ag[ks], gb + ks * 512); ldsm4t(au[ks], gb + 8192 + ks * 512); }
        }
        uint32_t sb = s_xn + brow * 1040 + (warp * 64 + bch * 8) * 2;
        uint32_t sd = s_red + (warp * 160 + (2 * t4) * 20 + r) * 4;
        uint32_t sa = s_act + brow * 48 + (bch & 1) * 16;
        pin(sb); pin(sd); pin(sa);
        bar_sync_p<4, NALL>(lv);
        {
            uint32_t b0[4], b1[4];
            ldsm4(b0, sb); ldsm4(b1, sb + 64);
            float g0[4] = {}, g1[4] = {}, u0[4] = {}, u1[4] = {};
            mma16816(g0, ag[0], b0[0], b0[1]); mma16816(u0, au[0], b0[0], b0[1]);
            mma16816(g1, ag[2], b1[0], b1[1]); mma16816(u1, au[2], b1[0], b1[1]);
            mma16816(g0, ag[1], b0[2], b0[3]); mma16816(u0, au[1], b0[2], b0[3]);
            mma16816(g1, ag[3], b1[2], b1[3]); mma16816(u1, au[3], b1[2], b1[3]);
            sts32(sd, g0[0] + g1[0], pw);        sts32(sd + 80, g0[1] + g1[1], pw);
            sts32(sd + 32, g0[2] + g1[2], pw);   sts32(sd + 80 + 32, g0[3] + g1[3], pw);
            sts32(sd + 320, u0[0] + u1[0], pw);      sts32(sd + 320 + 80, u0[1] + u1[1], pw);
            sts32(sd + 320 + 32, u0[2] + u1[2], pw); sts32(sd + 320 + 80 + 32, u0[3] + u1[3], pw);
            bar_arrive_p<5, NCONS + 64>(lv);
        }
        {
            const int slot = (ITEM_WD + wg) % NSLOT;
            mbar_wait_p(bar_full + 8 * slot, ((ITEM_WD + wg) / NSLOT) & 1, lv);
            const int krow = (lane & 7) + ((lane >> 4) << 3);
            const uint32_t db = sbase + slot * SLOT_BYTES + wl * 2048 + krow * 128;
#pragma unroll
            for (int j = 0; j < 4; j++) ldsm4t(ad[j], db + (((2 * j + ((lane >> 3) & 1)) ^ (krow & 7)) << 4));
            bar_sync_p<6, NCONS + 64>(lv);
            uint32_t b[4];
            ldsm4(b, sa);
#pragma unroll
            for (int j = 0; j < 4; j++) {
                float acc[4] = {0.f, 0.f, 0.f, 0.f};
                mma16816(acc, ad[j], b[0], b[1]);
                st_tag2(p_in2 + (2 * j) * NFCTA * 16, acc[0], acc[1], tag, pw);
                st_tag2(p_in2 + (2 * j + 1) * NFCTA * 16, acc[2], acc[3], tag, pw);
            }
            bar_arrive_p<9, NCONS + 32>(lv);
        }
    }
    if (lv) return;

    {
        const int hw = (tid >> 5) - 9;
        const int red_b = 2 * (c >> 6) + ((lane >> 3) & 1);
        const int red_n = 8 * (c & 63) + 2 * t4 + ((lane >> 4) & 1);
        const float x_res = __bfloat162float(x[red_b * DM + red_n]);
        const int cta0 = (hw * 8 + (c >> 4)) * 4, hh = (c >> 2) & 3;
        const float* q_po = &g_po[(cta0 * 4 + hh) * DH + lane * 4];
        const float* q_pml = &g_pml[(cta0 * 4 + hh) * 2];
        const float* q_in1 = &g_in1[(c * 32 + r) * 16 + 4 * t4];
        float* p_h = &g_h[((lane & 4) ? HREP / 2 : 0) * (NB * DM) + red_b * DM + red_n];
        const float* q_h = &g_h[(c % HREP) * (NB * DM) + hw * DM + lane * 4];
        const float* q_in2 = &g_in2[(c * NFCTA + r) * 16 + 4 * t4];
        __nv_bfloat16* p_out = out + red_b * DM + red_n;
        uint32_t s_ofw = s_of + (hw * 136 + lane * 4) * 2, s_hn = s_xn + hw * 1040 + lane * 8;
        uint32_t s_gu = s_red + (((hw & 1) * 2 + (lane >> 4)) * 20 + (lane & 15)) * 4;
        uint32_t s_actw = s_act + (((hw & 1) * 2 + (lane >> 4)) * 24 + (lane & 15)) * 2;
        pin(q_po); pin(q_pml); pin(q_in1); pin(p_h); pin(q_h); pin(q_in2); pin(p_out); pin(s_ofw); pin(s_hn); pin(s_gu); pin(s_actw);

#pragma unroll 1
        for (int pass = 0; pass < 2; pass++) {
            asm volatile("mov.u32 %0, %1;" : "=r"(lv) : "r"(pass));
            if (lv) {
                if (hw == 0) {
                    uint32_t it = 0;
                    while (true) {
                        const int seen = (int)(ld_rlx1(&g_count) - epoch * NCTA);
                        if (lane == 0) asm volatile("st.volatile.shared.u32 [%0], %1;" ::"r"(sbase + SM_CNT), "r"(seen) : "memory");
                        if (seen >= NCTA) break;
                        __nanosleep(seen > 0 ? 100 : 1000);
                        if (++it > SPIN_LIMIT) __trap();
                    }
                }
                asm volatile("bar.sync 10, 128;" ::: "memory");
            }
            {
                PollSet<4, 4 * DH, 4, 8> ps;
                poll1(ps, q_po, q_pml, tag, lv);
                const uint4 (&ov)[4] = ps.v;
                const uint2 (&ml)[4] = ps.m;
                const float M = fmaxf(fmaxf(u2f(ml[0].x), u2f(ml[1].x)), fmaxf(u2f(ml[2].x), u2f(ml[3].x)));
                const float e0 = ex2((u2f(ml[0].x) - M) * LOG2E), e1 = ex2((u2f(ml[1].x) - M) * LOG2E);
                const float e2 = ex2((u2f(ml[2].x) - M) * LOG2E), e3 = ex2((u2f(ml[3].x) - M) * LOG2E);
                const float inv = rcp_approx(fmaf(e0, u2f(ml[0].y), e1 * u2f(ml[1].y)) + fmaf(e2, u2f(ml[2].y), e3 * u2f(ml[3].y)));
                const float a0 = fmaf(e0, u2f(ov[0].x), e1 * u2f(ov[1].x)) + fmaf(e2, u2f(ov[2].x), e3 * u2f(ov[3].x));
                const float a1 = fmaf(e0, u2f(ov[0].y), e1 * u2f(ov[1].y)) + fmaf(e2, u2f(ov[2].y), e3 * u2f(ov[3].y));
                const float a2 = fmaf(e0, u2f(ov[0].z), e1 * u2f(ov[1].z)) + fmaf(e2, u2f(ov[2].z), e3 * u2f(ov[3].z));
                const float a3 = fmaf(e0, u2f(ov[0].w), e1 * u2f(ov[1].w)) + fmaf(e2, u2f(ov[2].w), e3 * u2f(ov[3].w));
                sts64(s_ofw, pack_bf16(a0 * inv, a1 * inv), pack_bf16(a2 * inv, a3 * inv), lv);
                bar_arrive_p<3, NALL>(lv);
            }
            float h_res = 0.f;
            if (hw == 3 || !lv) {
                bar_sync_p<8, NCONS + 32>(lv);
                if (lv) spin_cycles(POLL_DELAY);
                const float kk = inbox_reduce<4>(q_in1, tag, lv, lane);
                h_res = bf16r(x_res + bf16r(kk));
#pragma unroll
                for (int rp = 0; rp < HREP / 2; rp++) st_tag1(p_h + rp * (NB * DM), h_res, tag, lv);
                bar_arrive_p<7, 128>(lv);
            }
            if (hw != 3) bar_sync_p<7, 128>(lv);
            if (lv) spin_cycles(POLL_DELAY);
            if (c < NFCTA) {
                PollSet<4, 128, 0, 0> ps;
                poll1(ps, q_h, q_h, tag, lv);
                const uint4 (&u)[4] = ps.v;
                float v[16];
#pragma unroll
                for (int k = 0; k < 4; k++) {
                    v[4 * k + 0] = u2f(u[k].x & 0xffff0000u); v[4 * k + 1] = u2f(u[k].y & 0xffff0000u);
                    v[4 * k + 2] = u2f(u[k].z & 0xffff0000u); v[4 * k + 3] = u2f(u[k].w & 0xffff0000u);
                }
                warp_layernorm_store(v, __shfl_sync(0xffffffffu, v[0], 0), s_hn, lv);
                bar_arrive_p<4, NALL>(lv);
                if (hw < 2 || !lv) {
                    bar_sync_p<5, NCONS + 64>(lv);
                    float gw[8], uw[8];
#pragma unroll
                    for (int w = 0; w < 8; w++) { gw[w] = lds32(s_gu + w * 640); uw[w] = lds32(s_gu + w * 640 + 320); }
                    const float g = bf16r(((gw[0] + gw[1]) + (gw[2] + gw[3])) + ((gw[4] + gw[5]) + (gw[6] + gw[7])));
                    const float u_ = bf16r(((uw[0] + uw[1]) + (uw[2] + uw[3])) + ((uw[4] + uw[5]) + (uw[6] + uw[7])));
                    const float inner = 0.7978845608028654f * fmaf(0.044715f * g * g, g, g);
                    const float ge = bf16r(__fdividef(g, 1.f + __expf(-2.f * inner)));
                    sts16(s_actw, __bfloat16_as_ushort(__float2bfloat16_rn(ge * u_)), lv);
                    bar_arrive_p<6, NCONS + 64>(lv);
                }
            }
            if (hw == 3 || !lv) {
                if (c < NFCTA) bar_sync_p<9, NCONS + 32>(lv);
                if (lv) spin_cycles(POLL_DELAY);
                const float k2 = inbox_reduce<14>(q_in2, tag, lv, lane);
                if (lv && !(lane & 4)) *p_out = __float2bfloat16_rn(h_res + bf16r(k2));
                if (lv && c == 0 && lane == 0) {
                    asm volatile("st.relaxed.gpu.global.u32 [%0], %1;" ::"l"(&g_epoch), "r"(epoch + 1) : "memory");
                }
            }
        }
    }
}

typedef CUresult (*EncodeFn)(CUtensorMap*, CUtensorMapDataType, cuuint32_t, void*, const cuuint64_t*, const cuuint64_t*,
                             const cuuint32_t*, const cuuint32_t*, CUtensorMapInterleave, CUtensorMapSwizzle,
                             CUtensorMapL2promotion, CUtensorMapFloatOOBfill);

CUtensorMap make_map(EncodeFn enc, const void* base, int rank, const cuuint64_t* dims, const cuuint64_t* strides,
                     const cuuint32_t* box, CUtensorMapSwizzle sw, CUtensorMapL2promotion promo) {
    CUtensorMap tm;
    cuuint32_t es[3] = {1, 1, 1};
    enc(&tm, CU_TENSOR_MAP_DATA_TYPE_BFLOAT16, rank, const_cast<void*>(base), dims, strides, box, es,
        CU_TENSOR_MAP_INTERLEAVE_NONE, sw, promo, CU_TENSOR_MAP_FLOAT_OOB_FILL_NONE);
    return tm;
}

}

extern "C" void kernel_launch(void* const* d_in, const int* in_sizes, int n_in, void* d_out, int out_size) {
    (void)in_sizes; (void)n_in; (void)out_size;
    const void* x = d_in[0];
    const void* kc = d_in[1];
    const void* vc = d_in[2];
    const void* wq = d_in[3];
    const void* wo = d_in[4];
    const void* wg = d_in[6];
    const void* wu = d_in[7];
    const void* wd = d_in[8];

    static EncodeFn enc = nullptr;
    if (!enc) {
        void* fn = nullptr;
        cudaDriverEntryPointQueryResult qr;
        cudaGetDriverEntryPoint("cuTensorMapEncodeTiled", &fn, cudaEnableDefault, &qr);
        enc = reinterpret_cast<EncodeFn>(fn);
        cudaFuncSetAttribute(fused_decode_kernel, cudaFuncAttributeMaxDynamicSharedMemorySize, SMEM_BYTES);
    }
    const auto P256 = CU_TENSOR_MAP_L2_PROMOTION_L2_256B;
    CUtensorMap tmK, tmV, tmWq, tmWo, tmWg, tmWu, tmWd;
    {
        cuuint64_t dims[3] = {64, (cuuint64_t)NB * HKV * SK, 2};
        cuuint64_t str[2] = {256, 128};
        cuuint32_t box[3] = {64, 64, 2};
        tmK = make_map(enc, kc, 3, dims, str, box, CU_TENSOR_MAP_SWIZZLE_128B, P256);
        tmV = make_map(enc, vc, 3, dims, str, box, CU_TENSOR_MAP_SWIZZLE_128B, P256);
    }
    {
        cuuint64_t dims[2] = {HQ * DH, DM};
        cuuint64_t str[1] = {HQ * DH * 2};
        cuuint32_t box[2] = {32, 256};
        tmWq = make_map(enc, wq, 2, dims, str, box, CU_TENSOR_MAP_SWIZZLE_64B, P256);
    }
    {
        cuuint64_t dims[3] = {64, HQ * DH, 8};
        cuuint64_t str[2] = {DM * 2, 128};
        cuuint32_t box[3] = {64, 128, 1};
        tmWo = make_map(enc, wo, 3, dims, str, box, CU_TENSOR_MAP_SWIZZLE_128B, P256);
    }
    {
        cuuint64_t dims[2] = {FF, DM};
        cuuint64_t str[1] = {FF * 2};
        cuuint32_t box[2] = {16, 256};
        tmWg = make_map(enc, wg, 2, dims, str, box, CU_TENSOR_MAP_SWIZZLE_32B, P256);
        tmWu = make_map(enc, wu, 2, dims, str, box, CU_TENSOR_MAP_SWIZZLE_32B, P256);
    }
    {
        cuuint64_t dims[3] = {64, FF, 8};
        cuuint64_t str[2] = {DM * 2, 128};
        cuuint32_t box[3] = {64, 16, 4};
        tmWd = make_map(enc, wd, 3, dims, str, box, CU_TENSOR_MAP_SWIZZLE_128B, P256);
    }
    cudaLaunchConfig_t cfg = {};
    cfg.gridDim = dim3(NCTA);
    cfg.blockDim = dim3(NTHREADS);
    cfg.dynamicSmemBytes = SMEM_BYTES;
    cfg.stream = cudaStreamPerThread;
    cudaLaunchAttribute attr[1];
    attr[0].id = cudaLaunchAttributeCooperative;
    attr[0].val.cooperative = 1;
    cfg.attrs = attr;
    cfg.numAttrs = 1;
    cudaLaunchKernelEx(&cfg, fused_decode_kernel, tmK, tmV, tmWq, tmWo, tmWg, tmWu, tmWd, (const __nv_bfloat16*)x,
                       (__nv_bfloat16*)d_out);
}
```

```cpp
#include <cuda_runtime.h>
#include <cuda_bf16.h>
#include <cuda.h>
#include <stdint.h>

namespace {

constexpr int NB = 4, DM = 512, HQ = 32, HKV = 8, SK = 8192, DH = 128, FF = 1792;
constexpr int NCTA = 128;
constexpr int NSPLIT = 4;
constexpr int TILE = 128;
constexpr int NTILE = SK / NSPLIT / TILE;
constexpr int SLOT_BYTES = 16384;
constexpr int NSLOT = 12;
constexpr int ITEM_WO = 2 + 4 * NTILE;
constexpr int ITEM_GU = ITEM_WO + 2;
constexpr int ITEM_WD = ITEM_WO + 4;
constexpr int NFCTA = FF / 16;
constexpr int HREP = 4;
constexpr int NCONS = 256;
constexpr int NHELP = 4;
constexpr int NTHREADS = NCONS + 32 + 32 * NHELP;
constexpr int NALL = NCONS + 32 * NHELP;

constexpr int WINDOW = 4;
constexpr int WINDOW_EG = 5;
constexpr int EG_COUNT = 8;
constexpr int WINDOW_T = 4;
constexpr int TRIGGER = 96;
constexpr int POLL_DELAY1 = 300;
constexpr int POLL_DELAY = 450;
constexpr uint32_t SPIN_LIMIT = 1u << 22;

constexpr int SM_MRG = NSLOT * SLOT_BYTES;
constexpr int SM_ML = SM_MRG + 8 * 4 * 136 * 4;
constexpr int SM_XN = SM_ML + 8 * 4 * 2 * 4;
constexpr int SM_QS = SM_XN + 4 * 520 * 2;
constexpr int SM_OF = SM_QS + 4 * 136 * 2;
constexpr int SM_ACT = SM_OF + 4 * 136 * 2;
constexpr int SM_BAR = SM_ACT + 4 * 24 * 2;
constexpr int SM_CNT = SM_BAR + 2 * NSLOT * 8;
constexpr int SM_WBAR = SM_CNT + 16;
constexpr int SM_TOTAL = SM_WBAR + 80;
constexpr int SMEM_BYTES = SM_TOTAL + 1024;

__device__ unsigned g_epoch;
__device__ unsigned g_count;
__device__ __align__(128) float g_q[NB * HQ * DH];
__device__ __align__(128) float g_po[NCTA * 4 * DH];
__device__ __align__(128) float g_pml[NCTA * 4 * 2];
__device__ __align__(128) float g_in1[NCTA * 32 * 16];
__device__ __align__(128) float g_h[HREP * NB * DM];
__device__ __align__(128) float g_in2[NCTA * NFCTA * 16];

__device__ __forceinline__ uint32_t smem_u32(const void* p) { return (uint32_t)__cvta_generic_to_shared(p); }
__device__ __forceinline__ void mbar_init(uint32_t bar, uint32_t cnt) {
    asm volatile("mbarrier.init.shared::cta.b64 [%0], %1;" ::"r"(bar), "r"(cnt) : "memory");
}
__device__ __forceinline__ void mbar_expect_tx(uint32_t bar, uint32_t bytes) {
    asm volatile("mbarrier.arrive.expect_tx.shared::cta.b64 _, [%0], %1;" ::"r"(bar), "r"(bytes) : "memory");
}
__device__ __forceinline__ void mbar_arrive(uint32_t bar) {
    asm volatile("mbarrier.arrive.shared::cta.b64 _, [%0];" ::"r"(bar) : "memory");
}
__device__ __forceinline__ void mbar_wait(uint32_t bar, uint32_t parity) {
    uint32_t done = 0, it = 0;
    while (true) {
        asm volatile("{\n.reg .pred p;\nmbarrier.try_wait.parity.shared::cta.b64 p, [%1], %2;\nselp.u32 %0, 1, 0, p;\n}"
                     : "=r"(done) : "r"(bar), "r"(parity) : "memory");
        if (done) break;
        if (++it > SPIN_LIMIT) __trap();
    }
}
__device__ __forceinline__ void mbar_wait_p(uint32_t bar, uint32_t parity, uint32_t lv) {
    uint32_t it = 0;
    while (true) {
        uint32_t done;
        asm volatile("{\n.reg .pred p, q;\nsetp.ne.u32 q, %3, 0;\nsetp.eq.u32 p, %3, 0;\n"
                     "@q mbarrier.try_wait.parity.shared::cta.b64 p, [%1], %2;\nselp.u32 %0, 1, 0, p;\n}"
                     : "=r"(done) : "r"(bar), "r"(parity), "r"(lv) : "memory");
        if (done) break;
        if (++it > SPIN_LIMIT) __trap();
    }
}
__device__ __forceinline__ void tma2d(uint32_t dst, const CUtensorMap* tm, int c0, int c1, uint32_t bar, uint64_t pol) {
    asm volatile("cp.async.bulk.tensor.2d.shared::cluster.global.mbarrier::complete_tx::bytes.L2::cache_hint [%0], [%1, {%3, %4}], [%2], %5;"
                 ::"r"(dst), "l"(tm), "r"(bar), "r"(c0), "r"(c1), "l"(pol) : "memory");
}
__device__ __forceinline__ void tma3d(uint32_t dst, const CUtensorMap* tm, int c0, int c1, int c2, uint32_t bar, uint64_t pol) {
    asm volatile("cp.async.bulk.tensor.3d.shared::cluster.global.mbarrier::complete_tx::bytes.L2::cache_hint [%0], [%1, {%3, %4, %5}], [%2], %6;"
                 ::"r"(dst), "l"(tm), "r"(bar), "r"(c0), "r"(c1), "r"(c2), "l"(pol) : "memory");
}
__device__ __forceinline__ void tm_prefetch(const CUtensorMap* tm) {
    asm volatile("prefetch.tensormap [%0];" ::"l"(tm) : "memory");
}
__device__ __forceinline__ void ldsm4(uint32_t (&r)[4], uint32_t addr) {
    asm volatile("ldmatrix.sync.aligned.m8n8.x4.shared.b16 {%0,%1,%2,%3}, [%4];"
                 : "=r"(r[0]), "=r"(r[1]), "=r"(r[2]), "=r"(r[3]) : "r"(addr) : "memory");
}
__device__ __forceinline__ void ldsm4t(uint32_t (&r)[4], uint32_t addr) {
    asm volatile("ldmatrix.sync.aligned.m8n8.x4.trans.shared.b16 {%0,%1,%2,%3}, [%4];"
                 : "=r"(r[0]), "=r"(r[1]), "=r"(r[2]), "=r"(r[3]) : "r"(addr) : "memory");
}
__device__ __forceinline__ void mma16816(float (&c)[4], const uint32_t (&a)[4], uint32_t b0, uint32_t b1) {
    asm volatile("mma.sync.aligned.m16n8k16.row.col.f32.bf16.bf16.f32 {%0,%1,%2,%3}, {%4,%5,%6,%7}, {%8,%9}, {%0,%1,%2,%3};"
                 : "+f"(c[0]), "+f"(c[1]), "+f"(c[2]), "+f"(c[3])
                 : "r"(a[0]), "r"(a[1]), "r"(a[2]), "r"(a[3]), "r"(b0), "r"(b1));
}
__device__ __forceinline__ uint32_t movm_t(uint32_t a) {
    uint32_t d;
    asm volatile("movmatrix.sync.aligned.m8n8.trans.b16 %0, %1;" : "=r"(d) : "r"(a));
    return d;
}
__device__ __forceinline__ uint32_t pack_bf16(float lo, float hi) {
    uint32_t d;
    asm("cvt.rn.bf16x2.f32 %0, %1, %2;" : "=r"(d) : "f"(hi), "f"(lo));
    return d;
}
__device__ __forceinline__ float bf16r(float x) { return __bfloat162float(__float2bfloat16_rn(x)); }
__device__ __forceinline__ float bf_lo(uint32_t w) { return __uint_as_float(w << 16); }
__device__ __forceinline__ float bf_hi(uint32_t w) { return __uint_as_float(w & 0xffff0000u); }
__device__ __forceinline__ float ex2(float x) {
    float y;
    asm("ex2.approx.ftz.f32 %0, %1;" : "=f"(y) : "f"(x));
    return y;
}
__device__ __forceinline__ void cons_sync() { asm volatile("bar.sync 1, 256;" ::: "memory"); }
template <int ID, int CNT> __device__ __forceinline__ void bar_sync_p(uint32_t lv) {
    asm volatile("{\n.reg .pred q;\nsetp.ne.u32 q, %0, 0;\n@q bar.sync %1, %2;\n}" ::"r"(lv), "n"(ID), "n"(CNT) : "memory");
}
template <int ID, int CNT> __device__ __forceinline__ void bar_arrive_p(uint32_t lv) {
    asm volatile("{\n.reg .pred q;\nsetp.ne.u32 q, %0, 0;\n@q bar.arrive %1, %2;\n}" ::"r"(lv), "n"(ID), "n"(CNT) : "memory");
}
__device__ __forceinline__ void spin_cycles(uint32_t n) {
    const uint32_t t0 = (uint32_t)clock();
    while ((uint32_t)clock() - t0 < n) {}
}
__device__ __forceinline__ void sts32(uint32_t a, float v, uint32_t p) {
    asm volatile("{\n.reg .pred q;\nsetp.ne.u32 q, %2, 0;\n@q st.shared.f32 [%0], %1;\n}" ::"r"(a), "f"(v), "r"(p) : "memory");
}
__device__ __forceinline__ void sts16(uint32_t a, uint16_t v, uint32_t p) {
    asm volatile("{\n.reg .pred q;\nsetp.ne.u32 q, %2, 0;\n@q st.shared.u16 [%0], %1;\n}" ::"r"(a), "h"(v), "r"(p) : "memory");
}
__device__ __forceinline__ void sts64(uint32_t a, uint32_t x, uint32_t y, uint32_t p) {
    asm volatile("{\n.reg .pred q;\nsetp.ne.u32 q, %3, 0;\n@q st.shared.v2.u32 [%0], {%1, %2};\n}" ::"r"(a), "r"(x), "r"(y), "r"(p) : "memory");
}
__device__ __forceinline__ float lds32(uint32_t a) {
    float v; asm volatile("ld.shared.f32 %0, [%1];" : "=f"(v) : "r"(a) : "memory"); return v;
}
__device__ __forceinline__ float2 lds64(uint32_t a) {
    float2 v; asm volatile("ld.shared.v2.f32 {%0, %1}, [%2];" : "=f"(v.x), "=f"(v.y) : "r"(a) : "memory"); return v;
}

__device__ __forceinline__ float u2f(uint32_t u) { return __uint_as_float(u); }
__device__ __forceinline__ float tagf(float v, uint32_t tag) { return __uint_as_float((__float_as_uint(v) & ~1u) | tag); }
__device__ __forceinline__ void st_tag1(float* ptr, float v, uint32_t tag, uint32_t p) {
    asm volatile("{\n.reg .pred q;\nsetp.ne.u32 q, %2, 0;\n@q st.relaxed.gpu.global.f32 [%0], %1;\n}"
                 ::"l"(ptr), "f"(tagf(v, tag)), "r"(p) : "memory");
}
__device__ __forceinline__ void st_tag2(float* ptr, float a, float b, uint32_t tag, uint32_t p) {
    asm volatile("{\n.reg .pred q;\nsetp.ne.u32 q, %3, 0;\n@q st.relaxed.gpu.global.v2.f32 [%0], {%1, %2};\n}"
                 ::"l"(ptr), "f"(tagf(a, tag)), "f"(tagf(b, tag)), "r"(p) : "memory");
}
__device__ __forceinline__ void ld_rlx4(uint4& v, const float* ptr, uint32_t p) {
    asm volatile("{\n.reg .pred q;\nsetp.ne.u32 q, %5, 0;\n@q ld.relaxed.gpu.global.v4.u32 {%0,%1,%2,%3}, [%4];\n}"
                 : "+r"(v.x), "+r"(v.y), "+r"(v.z), "+r"(v.w) : "l"(ptr), "r"(p) : "memory");
}
__device__ __forceinline__ void ld_rlx2(uint2& v, const float* ptr, uint32_t p) {
    asm volatile("{\n.reg .pred q;\nsetp.ne.u32 q, %3, 0;\n@q ld.relaxed.gpu.global.v2.u32 {%0,%1}, [%2];\n}"
                 : "+r"(v.x), "+r"(v.y) : "l"(ptr), "r"(p) : "memory");
}
__device__ __forceinline__ uint32_t ld_rlx1(const unsigned* p) {
    uint32_t v;
    asm volatile("ld.relaxed.gpu.global.u32 %0, [%1];" : "=r"(v) : "l"(p) : "memory");
    return v;
}
__device__ __forceinline__ uint32_t bad4(const uint4& v, uint32_t tag) {
    uint32_t u, w, r;
    asm("lop3.b32 %0, %1, %2, %3, 0x7E;" : "=r"(u) : "r"(v.x), "r"(v.y), "r"(tag));
    asm("lop3.b32 %0, %1, %2, %3, 0x7E;" : "=r"(w) : "r"(v.z), "r"(v.w), "r"(tag));
    asm("lop3.b32 %0, %1, %2, 1, 0xA8;" : "=r"(r) : "r"(u), "r"(w));
    return r;
}
__device__ __forceinline__ uint32_t bad2(const uint2& v, uint32_t tag) {
    uint32_t u;
    asm("lop3.b32 %0, %1, %2, %3, 0x7E;" : "=r"(u) : "r"(v.x), "r"(v.y), "r"(tag));
    return u & 1u;
}
template <typename T> __device__ __forceinline__ void pin(T*& p) { asm volatile("" : "+l"(p)); }
__device__ __forceinline__ void pin(uint32_t& v) { asm volatile("" : "+r"(v)); }
__device__ __forceinline__ float sqrt_approx(float x) { float y; asm("sqrt.approx.ftz.f32 %0, %1;" : "=f"(y) : "f"(x)); return y; }
__device__ __forceinline__ float rcp_approx(float x) { float y; asm("rcp.approx.ftz.f32 %0, %1;" : "=f"(y) : "f"(x)); return y; }
template <int NK, int KS, int NM, int MS>
struct PollSet {
    uint4 v[NK]; uint2 m[NM > 0 ? NM : 1]; uint32_t bad[NK], badm[NM > 0 ? NM : 1];
    __device__ __forceinline__ void init(uint32_t tag, uint32_t lv) {
#pragma unroll
        for (int k = 0; k < NK; k++) { v[k] = make_uint4(tag, tag, tag, tag); bad[k] = lv; }
#pragma unroll
        for (int k = 0; k < NM; k++) { m[k] = make_uint2(tag, tag); badm[k] = lv; }
    }
    __device__ __forceinline__ void issue(const float* src, const float* src2) {
#pragma unroll
        for (int k = 0; k < NK; k++) ld_rlx4(v[k], src + k * KS, bad[k]);
#pragma unroll
        for (int k = 0; k < NM; k++) ld_rlx2(m[k], src2 + k * MS, badm[k]);
    }
    __device__ __forceinline__ bool complete(uint32_t tag) {
        uint32_t any = 0;
#pragma unroll
        for (int k = 0; k < NK; k++) { bad[k] = bad4(v[k], tag); any |= bad[k]; }
#pragma unroll
        for (int k = 0; k < NM; k++) { badm[k] = bad2(m[k], tag); any |= badm[k]; }
        return !__any_sync(0xffffffffu, any);
    }
};
constexpr float LOG2E = 1.4426950408889634f;

__device__ __forceinline__ void warp_layernorm_store(const float (&v)[16], float c, uint32_t dst, uint32_t p) {
    float s1[4], s2[4];
#pragma unroll
    for (int k = 0; k < 4; k++) {
        const float d0 = v[4 * k] - c, d1 = v[4 * k + 1] - c, d2 = v[4 * k + 2] - c, d3 = v[4 * k + 3] - c;
        s1[k] = (d0 + d1) + (d2 + d3);
        s2[k] = fmaf(d0, d0, d1 * d1) + fmaf(d2, d2, d3 * d3);
    }
    float t1 = (s1[0] + s1[1]) + (s1[2] + s1[3]), t2 = (s2[0] + s2[1]) + (s2[2] + s2[3]);
#pragma unroll
    for (int o = 16; o > 0; o >>= 1) {
        t1 += __shfl_xor_sync(0xffffffffu, t1, o);
        t2 += __shfl_xor_sync(0xffffffffu, t2, o);
    }
    const float md = t1 * (1.f / 512.f);
    const float mean = bf16r(c + md);
    const float var = bf16r(fmaxf(fmaf(-md, md, t2 * (1.f / 512.f)), 0.f));
    const float inv = rcp_approx(bf16r(sqrt_approx(bf16r(var + 1e-5f))));
#pragma unroll
    for (int k = 0; k < 4; k++) {
        const uint32_t t01 = pack_bf16(v[4 * k + 0] - mean, v[4 * k + 1] - mean);
        const uint32_t t23 = pack_bf16(v[4 * k + 2] - mean, v[4 * k + 3] - mean);
        sts64(dst + k * 256, pack_bf16(bf_lo(t01) * inv, bf_hi(t01) * inv), pack_bf16(bf_lo(t23) * inv, bf_hi(t23) * inv), p);
    }
}

template <class PS>
__device__ __forceinline__ void poll1(PS& ps, const float* src, const float* src2, uint32_t tag, uint32_t lv) {
    ps.init(tag, lv);
    uint32_t it = 0;
    while (true) {
        ps.issue(src, src2);
        if (ps.complete(tag)) break;
        if (++it > SPIN_LIMIT) __trap();
    }
}
template <int NK>
__device__ __forceinline__ float inbox_reduce(const float* src, uint32_t tag, uint32_t lv, int lane) {
    PollSet<NK, 128, 0, 0> ps;
    poll1(ps, src, src, tag, lv);
    float a = 0.f, b = 0.f, c = 0.f, d = 0.f, a2 = 0.f, b2 = 0.f, c2 = 0.f, d2 = 0.f;
#pragma unroll
    for (int k = 0; k < NK; k += 2) {
        a += u2f(ps.v[k].x); b += u2f(ps.v[k].y); c += u2f(ps.v[k].z); d += u2f(ps.v[k].w);
        a2 += u2f(ps.v[k + 1].x); b2 += u2f(ps.v[k + 1].y); c2 += u2f(ps.v[k + 1].z); d2 += u2f(ps.v[k + 1].w);
    }
    a += a2; b += b2; c += c2; d += d2;
    const bool hi = lane & 16, h2 = lane & 8;
    float k0 = hi ? c : a, k1 = hi ? d : b;
    k0 += __shfl_xor_sync(0xffffffffu, hi ? a : c, 16);
    k1 += __shfl_xor_sync(0xffffffffu, hi ? b : d, 16);
    float kk = h2 ? k1 : k0;
    kk += __shfl_xor_sync(0xffffffffu, h2 ? k0 : k1, 8);
    kk += __shfl_xor_sync(0xffffffffu, kk, 4);
    return kk;
}


__global__ void __launch_bounds__(NTHREADS, 1)
fused_decode_kernel(const __grid_constant__ CUtensorMap tmK, const __grid_constant__ CUtensorMap tmV,
                    const __grid_constant__ CUtensorMap tmWq, const __grid_constant__ CUtensorMap tmWo,
                    const __grid_constant__ CUtensorMap tmWg, const __grid_constant__ CUtensorMap tmWu,
                    const __grid_constant__ CUtensorMap tmWd,
                    const __nv_bfloat16* __restrict__ x, __nv_bfloat16* __restrict__ out) {
    extern __shared__ uint8_t smem_raw[];
    const uint32_t sbase = (smem_u32(smem_raw) + 1023u) & ~1023u;
    const uint32_t bar_full = sbase + SM_BAR, bar_empty = bar_full + NSLOT * 8;
    const int tid = threadIdx.x, lane = tid & 31;
    const int c = blockIdx.x;
    const int row0 = (c >> 2) * SK + (c & 3) * (SK / NSPLIT);
    uint64_t pol_stream = 0;
    if (tid == NCONS) {
        tm_prefetch(&tmWq); tm_prefetch(&tmK); tm_prefetch(&tmV);
        for (int i = 0; i < 4; i++) mbar_init(bar_full + 8 * i, 1);
        asm volatile("fence.proxy.async.shared::cta;" ::: "memory");
        asm volatile("createpolicy.fractional.L2::evict_first.b64 %0, 1.0;" : "=l"(pol_stream));
        mbar_expect_tx(bar_full, SLOT_BYTES);
        tma2d(sbase, &tmWq, 32 * c, 0, bar_full, pol_stream);
        mbar_expect_tx(bar_full + 8, SLOT_BYTES);
        tma2d(sbase + SLOT_BYTES, &tmWq, 32 * c, 256, bar_full + 8, pol_stream);
        mbar_expect_tx(bar_full + 16, SLOT_BYTES);
        tma3d(sbase + 2 * SLOT_BYTES, &tmK, 0, row0, 0, bar_full + 16, pol_stream);
        mbar_expect_tx(bar_full + 24, SLOT_BYTES);
        tma3d(sbase + 3 * SLOT_BYTES, &tmK, 0, row0 + 64, 0, bar_full + 24, pol_stream);
        for (int i = 4; i < NSLOT; i++) mbar_init(bar_full + 8 * i, 1);
        for (int i = 0; i < NSLOT; i++) mbar_init(bar_empty + 8 * i, 4);
        for (int i = 0; i < 10; i++) mbar_init(sbase + SM_WBAR + 8 * i, 1);
        asm volatile("fence.proxy.async.shared::cta;" ::: "memory");
        asm volatile("st.volatile.shared.u32 [%0], %1;" ::"r"(sbase + SM_CNT), "r"(0) : "memory");
    }
    __syncthreads();

    if ((tid >> 5) == 8) {
        if (lane == 0) {
            auto acquire = [&](int i, int window) {
                if (i >= NSLOT) mbar_wait(bar_empty + 8 * (i % NSLOT), ((i / NSLOT) - 1) & 1);
                if (i >= window) { const int j = i - window; mbar_wait(bar_full + 8 * (j % NSLOT), (j / NSLOT) & 1); }
            };
            auto seen_count = [&]() {
                uint32_t seen;
                asm volatile("ld.volatile.shared.u32 %0, [%1];" : "=r"(seen) : "r"(sbase + SM_CNT) : "memory");
                return (int)seen;
            };
#pragma unroll 1
            for (int i = 4; i < ITEM_WO; i++) {
                const int slot = i % NSLOT;
                acquire(i, (i >= ITEM_WO - 24 && seen_count() >= EG_COUNT) ? WINDOW_EG : WINDOW);
                const int t = (i - 2) >> 2, sub = (i - 2) & 3;
                mbar_expect_tx(bar_full + 8 * slot, SLOT_BYTES);
                tma3d(sbase + slot * SLOT_BYTES, (sub & 2) ? &tmV : &tmK, 0, row0 + t * TILE + (sub & 1) * 64, 0,
                      bar_full + 8 * slot, pol_stream);
            }
            asm volatile("red.relaxed.gpu.global.add.u32 [%0], 1;" ::"l"(&g_count) : "memory");
            {
                uint32_t it = 0;
                while (seen_count() < TRIGGER) {
                    __nanosleep(20);
                    if (++it > SPIN_LIMIT) __trap();
                }
            }
            const int npiece = (c < NFCTA) ? 10 : 4;
#pragma unroll 1
            for (int j = 0; j < npiece; j++) {
                const int item = j < 4 ? ITEM_WO + (j >> 1) : (j < 8 ? ITEM_GU + ((j - 4) >> 1) : ITEM_WD + (j - 8));
                const int slot = item % NSLOT;
                mbar_wait(bar_empty + 8 * slot, ((item / NSLOT) - 1) & 1);
                if (j >= WINDOW_T) mbar_wait(sbase + SM_WBAR + 8 * (j - WINDOW_T), 0);
                else if (j < 2) { const int jj = ITEM_WO - 2 + j; mbar_wait(bar_full + 8 * (jj % NSLOT), (jj / NSLOT) & 1); }
                const uint32_t fb = sbase + SM_WBAR + 8 * j, dst = sbase + slot * SLOT_BYTES + ((j < 8) ? (j & 1) * 8192 : 0);
                mbar_expect_tx(fb, 8192);
                if (j < 4) tma3d(dst, &tmWo, 0, 128 * (c >> 2) + 64 * (j & 1), 2 * (c & 3) + (j >> 1), fb, pol_stream);
                else if (j < 8) tma2d(dst, (j & 1) ? &tmWu : &tmWg, 16 * c, 256 * ((j - 4) >> 1), fb, pol_stream);
                else tma3d(dst, &tmWd, 0, 16 * c, 4 * (j - 8), fb, pol_stream);
            }
        }
        return;
    }

    uint32_t lv;
    asm volatile("mov.u32 %0, %1;" : "=r"(lv) : "r"((tid < NCONS) ? 1u : 0u));
    const int warp = lv ? (tid >> 5) : 0;
    const int vtid = warp * 32 + lane;
    const int r = lane >> 2, t4 = lane & 3;
    const int wg = warp >> 2, wl = warp & 3;
    const uint32_t s_red = sbase + SM_MRG, s_ml = sbase + SM_ML, s_xn = sbase + SM_XN;
    const uint32_t s_qs = sbase + SM_QS, s_of = sbase + SM_OF, s_act = sbase + SM_ACT;
    const int brow = lane & 3, bch = lane >> 3;

    uint2 xw[4];
#pragma unroll
    for (int k = 0; k < 4; k++) {
        xw[k] = make_uint2(0u, 0u);
        asm volatile("{\n.reg .pred q;\nsetp.ne.u32 q, %3, 0;\n@q ld.global.nc.v2.u32 {%0, %1}, [%2];\n}"
                     : "+r"(xw[k].x), "+r"(xw[k].y) : "l"(x + (warp & 3) * DM + k * 128 + lane * 4), "r"((uint32_t)(lv && warp < NB)));
    }
    const unsigned epoch = ld_rlx1(&g_epoch);
    uint32_t tag = 0;

    float* p_po = &g_po[(c * 4 + (vtid >> 6)) * DH + (vtid & 63) * 2];
    float* p_pml = &g_pml[(c * 4 + (vtid >> 6)) * 2];
    float* p_in1 = &g_in1[((t4 * 64 + 16 * (c & 3) + 2 * warp) * 32 + (c >> 2)) * 16 + 2 * r];
    float* p_in2 = &g_in2[((t4 * 64 + 8 * warp) * NFCTA + (c < NFCTA ? c : 0)) * 16 + 2 * r];
    pin(p_po); pin(p_pml); pin(p_in1); pin(p_in2);

    float o[8][4];
#pragma unroll
    for (int j = 0; j < 8; j++) { o[j][0] = o[j][1] = o[j][2] = o[j][3] = 0.f; }
    float mfin0 = 0.f, mfin1 = 0.f;

    if (lv) {
        if (warp < NB) {
            float v[16];
#pragma unroll
            for (int k = 0; k < 4; k++) {
                const uint2 w = xw[k];
                v[4 * k + 0] = bf_lo(w.x); v[4 * k + 1] = bf_hi(w.x); v[4 * k + 2] = bf_lo(w.y); v[4 * k + 3] = bf_hi(w.y);
            }
            warp_layernorm_store(v, __shfl_sync(0xffffffffu, v[0], 0), s_xn + warp * 1040 + lane * 8, 1u);
        }
        cons_sync();
        asm volatile("lop3.b32 %0, %1, 1, 1, 0x6A;" : "=r"(tag) : "r"(epoch));

        mbar_wait(bar_full + 8 * wg, 0);
        {
            float acc[2][4] = {};
#pragma unroll
            for (int kp = 0; kp < 2; kp++) {
                uint32_t b[4];
                ldsm4(b, s_xn + brow * 1040 + (warp * 64 + kp * 32 + bch * 8) * 2);
#pragma unroll
                for (int k2 = 0; k2 < 2; k2++) {
                    const int krow = warp * 64 + kp * 32 + k2 * 16 + (lane & 7) + ((lane >> 4) << 3);
#pragma unroll
                    for (int mt = 0; mt < 2; mt++) {
                        const int chunk = mt * 2 + ((lane >> 3) & 1);
                        uint32_t a[4];
                        ldsm4t(a, sbase + krow * 64 + ((chunk ^ ((krow >> 1) & 3)) << 4));
                        mma16816(acc[mt], a, b[2 * k2], b[2 * k2 + 1]);
                    }
                }
            }
            __syncwarp();
            if (lane == 0) mbar_arrive(bar_empty + 8 * wg);
            const uint32_t pq = t4 < 2;
#pragma unroll
            for (int mt = 0; mt < 2; mt++) {
                const uint32_t dst = s_red + (warp * 144 + (2 * t4) * 36 + mt * 16 + r) * 4;
                sts32(dst, acc[mt][0], pq); sts32(dst + 144, acc[mt][1], pq);
                sts32(dst + 32, acc[mt][2], pq); sts32(dst + 144 + 32, acc[mt][3], pq);
            }
            cons_sync();
            if (tid < 128) {
                float s = 0.f;
#pragma unroll
                for (int w = 0; w < 8; w++) s += lds32(s_red + (w * 144 + warp * 36 + lane) * 4);
                st_tag1(&g_q[warp * (HQ * DH) + 32 * c + lane], bf16r(s), tag, 1u);
                const int g = c >> 2;
                const float* src = &g_q[(g >> 3) * (HQ * DH) + (g & 7) * 512 + tid * 4];
                uint4 v;
                uint32_t it = 0;
                while (true) {
                    ld_rlx4(v, src, 1u);
                    if (!(bad4(v, tag) & 1)) break;
                    if (++it > SPIN_LIMIT) __trap();
                }
                sts64(s_qs + (warp * 136 + lane * 4) * 2, (v.x >> 16) | (v.y & 0xffff0000u), (v.z >> 16) | (v.w & 0xffff0000u), 1u);
            }
            cons_sync();
        }

        uint32_t qf[8][2];
#pragma unroll
        for (int j = 0; j < 8; j += 2) {
            uint32_t b[4];
            ldsm4(b, s_qs + brow * 272 + (j * 16 + bch * 8) * 2);
            qf[j][0] = b[0]; qf[j][1] = b[1]; qf[j + 1][0] = b[2]; qf[j + 1][1] = b[3];
        }
        const int krow = wl * 16 + (lane & 7) + (((lane >> 3) & 1) << 3);
        const int kch = lane >> 4;
        const int vrow = wl * 16 + (lane & 7) + ((lane >> 4) << 3);
        const int vch = (lane >> 3) & 1;
        const float scale = 0.08838834764831845f;
        float m0 = -INFINITY, m1 = -INFINITY, l0 = 0.f, l1 = 0.f;

#pragma unroll 1
        for (int t = 0; t < NTILE; t++) {
            const int ik = 2 + 4 * t + wg, iv = ik + 2;
            const int sk = ik % NSLOT, sv = iv % NSLOT;
            mbar_wait(bar_full + 8 * sk, (ik / NSLOT) & 1);
            float sa[4] = {0.f, 0.f, 0.f, 0.f}, sb[4] = {0.f, 0.f, 0.f, 0.f};
            const uint32_t kb = sbase + sk * SLOT_BYTES + krow * 128;
#pragma unroll
            for (int j = 0; j < 8; j += 2) {
                uint32_t a0[4], a1[4];
                ldsm4(a0, kb + (j >> 2) * 8192 + (((((j & 3) << 1) + kch) ^ (krow & 7)) << 4));
                ldsm4(a1, kb + ((j + 1) >> 2) * 8192 + ((((((j + 1) & 3) << 1) + kch) ^ (krow & 7)) << 4));
                mma16816(sa, a0, qf[j][0], qf[j][1]);
                mma16816(sb, a1, qf[j + 1][0], qf[j + 1][1]);
            }
            __syncwarp();
            if (lane == 0) mbar_arrive(bar_empty + 8 * sk);
            const float s0 = bf16r(bf16r(sa[0] + sb[0]) * scale), s1 = bf16r(bf16r(sa[1] + sb[1]) * scale);
            const float s2 = bf16r(bf16r(sa[2] + sb[2]) * scale), s3 = bf16r(bf16r(sa[3] + sb[3]) * scale);
            float x0 = fmaxf(fmaxf(s0, s2), m0), x1 = fmaxf(fmaxf(s1, s3), m1);
#pragma unroll
            for (int off = 4; off < 32; off <<= 1) {
                x0 = fmaxf(x0, __shfl_xor_sync(0xffffffffu, x0, off));
                x1 = fmaxf(x1, __shfl_xor_sync(0xffffffffu, x1, off));
            }
            if (t == NTILE - 1) {
                if (r == 0 && t4 < 2) asm volatile("st.shared.v2.f32 [%0], {%1, %2};" ::"r"(s_ml + (warp * 4 + t4 * 2) * 4), "f"(x0), "f"(x1) : "memory");
                cons_sync();
#pragma unroll
                for (int w = 0; w < 8; w++) {
                    const float2 mw = lds64(s_ml + (w * 4 + (t4 & 1) * 2) * 4);
                    x0 = fmaxf(x0, mw.x); x1 = fmaxf(x1, mw.y);
                }
            }
            if (__any_sync(0xffffffffu, (x0 > m0) || (x1 > m1))) {
                const float a0 = ex2((m0 - x0) * LOG2E), a1 = ex2((m1 - x1) * LOG2E);
                m0 = x0; m1 = x1;
                l0 *= a0; l1 *= a1;
#pragma unroll
                for (int j = 0; j < 8; j++) { o[j][0] *= a0; o[j][1] *= a1; o[j][2] *= a0; o[j][3] *= a1; }
            }
            const float p0 = ex2((s0 - m0) * LOG2E), p1 = ex2((s1 - m1) * LOG2E);
            const float p2 = ex2((s2 - m0) * LOG2E), p3 = ex2((s3 - m1) * LOG2E);
            l0 += p0 + p2; l1 += p1 + p3;
            const uint32_t pb0 = movm_t(pack_bf16(p0, p1));
            const uint32_t pb1 = movm_t(pack_bf16(p2, p3));
            if (t == NTILE - 1) {
#pragma unroll
                for (int off = 4; off < 32; off <<= 1) {
                    l0 += __shfl_xor_sync(0xffffffffu, l0, off);
                    l1 += __shfl_xor_sync(0xffffffffu, l1, off);
                }
                if (r == 0 && t4 < 2) asm volatile("st.shared.v2.f32 [%0], {%1, %2};" ::"r"(s_ml + 128 + (warp * 4 + t4 * 2) * 4), "f"(l0), "f"(l1) : "memory");
            }

            mbar_wait(bar_full + 8 * sv, (iv / NSLOT) & 1);
            const uint32_t vb = sbase + sv * SLOT_BYTES + vrow * 128;
#pragma unroll
            for (int j = 0; j < 8; j++) {
                uint32_t a[4];
                ldsm4t(a, vb + (j >> 2) * 8192 + (((((j & 3) << 1) + vch) ^ (vrow & 7)) << 4));
                mma16816(o[j], a, pb0, pb1);
            }
            __syncwarp();
            if (lane == 0) mbar_arrive(bar_empty + 8 * sv);
        }
        mfin0 = m0; mfin1 = m1;
    } else {
        tag = (epoch & 1u) ^ 1u;
        __nanosleep(6000);
        const int wt = tid - (NCONS + 32);
        const float z = __uint_as_float(tag ^ 1u);
        auto st4 = [&](float* p) {
            asm volatile("st.relaxed.gpu.global.v4.f32 [%0], {%1, %1, %1, %1};" ::"l"(p), "f"(z) : "memory");
        };
        st4(&g_po[c * 512 + wt * 4]);
        st4(&g_in1[((((wt >> 2) >> 4) * 64 + 16 * (c & 3) + ((wt >> 2) & 15)) * 32 + (c >> 2)) * 16 + (wt & 3) * 4]);
        if (c < NFCTA)
            for (int i = wt; i < 512; i += 128) st4(&g_in2[((i >> 2) * NFCTA + c) * 16 + (i & 3) * 4]);
        if (wt < 16) st4(&g_h[(wt >> 2) * (NB * DM) + (2 * (c >> 6) + ((wt >> 1) & 1)) * DM + 8 * (c & 63) + (wt & 1) * 4]);
        else if (wt < 18) st4(&g_pml[c * 8 + (wt - 16) * 4]);
        asm volatile("bar.arrive 2, %0;" ::"n"(NALL) : "memory");
    }

    const uint32_t pw = lv && (t4 < 2);
    {
        const uint32_t dst = s_red + (warp * 544 + (2 * t4) * 136 + r) * 4;
#pragma unroll
        for (int j = 0; j < 8; j++) {
            sts32(dst + j * 64, o[j][0], pw);
            sts32(dst + 544 + j * 64, o[j][1], pw);
            sts32(dst + j * 64 + 32, o[j][2], pw);
            sts32(dst + 544 + j * 64 + 32, o[j][3], pw);
        }
        const int h = vtid >> 6;
        const uint32_t src = s_red + (h * 136 + (vtid & 63) * 2) * 4;
        const float Mh = __shfl_sync(0xffffffffu, (h & 1) ? mfin1 : mfin0, h >> 1);
        bar_sync_p<2, NALL>(lv);
        float2 ov[8]; float lw[8];
#pragma unroll
        for (int w = 0; w < 8; w++) { ov[w] = lds64(src + w * 2176); lw[w] = lds32(s_ml + 128 + (w * 4 + h) * 4); }
        const float a0 = ((ov[0].x + ov[1].x) + (ov[2].x + ov[3].x)) + ((ov[4].x + ov[5].x) + (ov[6].x + ov[7].x));
        const float a1 = ((ov[0].y + ov[1].y) + (ov[2].y + ov[3].y)) + ((ov[4].y + ov[5].y) + (ov[6].y + ov[7].y));
        const float L = ((lw[0] + lw[1]) + (lw[2] + lw[3])) + ((lw[4] + lw[5]) + (lw[6] + lw[7]));
        st_tag2(p_po, a0, a1, tag, lv);
        st_tag2(p_pml, Mh, L, tag, lv && (vtid & 63) == 0);
        bar_arrive_p<11, NALL>(lv);
    }
    {
        const int slot = (ITEM_WO + wg) % NSLOT;
        mbar_wait_p(sbase + SM_WBAR + 8 * (2 * wg), 0, lv);
        mbar_wait_p(sbase + SM_WBAR + 8 * (2 * wg + 1), 0, lv);
        const int krow = (lane & 7) + ((lane >> 4) << 3);
        const uint32_t wb = sbase + slot * SLOT_BYTES + krow * 128 + ((((wl << 1) + ((lane >> 3) & 1)) ^ (krow & 7)) << 4);
        uint32_t a[8][4];
#pragma unroll
        for (int ks = 0; ks < 8; ks++) ldsm4t(a[ks], wb + ks * 2048);
        uint32_t sb = s_of + brow * 272 + bch * 16;
        pin(sb);
        bar_sync_p<3, NALL>(lv);
        uint32_t b[4][4];
#pragma unroll
        for (int kp = 0; kp < 4; kp++) ldsm4(b[kp], sb + kp * 64);
        float acc[4][4] = {};
#pragma unroll
        for (int kp = 0; kp < 4; kp++) {
            mma16816(acc[kp], a[2 * kp], b[kp][0], b[kp][1]);
            mma16816(acc[kp], a[2 * kp + 1], b[kp][2], b[kp][3]);
        }
        st_tag2(p_in1, (acc[0][0] + acc[1][0]) + (acc[2][0] + acc[3][0]), (acc[0][1] + acc[1][1]) + (acc[2][1] + acc[3][1]), tag, pw);
        st_tag2(p_in1 + 32 * 16, (acc[0][2] + acc[1][2]) + (acc[2][2] + acc[3][2]), (acc[0][3] + acc[1][3]) + (acc[2][3] + acc[3][3]), tag, pw);
        bar_arrive_p<8, NCONS + 32>(lv);
    }
    if (c < NFCTA) {
        uint32_t ag[4][4], au[4][4], ad[4][4];
        {
            const int slot = (ITEM_GU + wg) % NSLOT;
            mbar_wait_p(sbase + SM_WBAR + 8 * (4 + 2 * wg), 0, lv);
            mbar_wait_p(sbase + SM_WBAR + 8 * (5 + 2 * wg), 0, lv);
            const int krow = wl * 64 + (lane & 7) + ((lane >> 4) << 3);
            const uint32_t gb = sbase + slot * SLOT_BYTES + krow * 32 + ((((lane >> 3) & 1) ^ ((krow >> 2) & 1)) << 4);
#pragma unroll
            for (int ks = 0; ks < 4; ks++) { ldsm4t(ag[ks], gb + ks * 512); ldsm4t(au[ks], gb + 8192 + ks * 512); }
        }
        uint32_t sb = s_xn + brow * 1040 + (warp * 64 + bch * 8) * 2;
        uint32_t sd = s_red + (warp * 160 + (2 * t4) * 20 + r) * 4;
        uint32_t sa = s_act + brow * 48 + (bch & 1) * 16;
        pin(sb); pin(sd); pin(sa);
        bar_sync_p<4, NALL>(lv);
        {
            uint32_t b0[4], b1[4];
            ldsm4(b0, sb); ldsm4(b1, sb + 64);
            float g0[4] = {}, g1[4] = {}, u0[4] = {}, u1[4] = {};
            mma16816(g0, ag[0], b0[0], b0[1]); mma16816(u0, au[0], b0[0], b0[1]);
            mma16816(g1, ag[2], b1[0], b1[1]); mma16816(u1, au[2], b1[0], b1[1]);
            mma16816(g0, ag[1], b0[2], b0[3]); mma16816(u0, au[1], b0[2], b0[3]);
            mma16816(g1, ag[3], b1[2], b1[3]); mma16816(u1, au[3], b1[2], b1[3]);
            sts32(sd, g0[0] + g1[0], pw);        sts32(sd + 80, g0[1] + g1[1], pw);
            sts32(sd + 32, g0[2] + g1[2], pw);   sts32(sd + 80 + 32, g0[3] + g1[3], pw);
            sts32(sd + 320, u0[0] + u1[0], pw);      sts32(sd + 320 + 80, u0[1] + u1[1], pw);
            sts32(sd + 320 + 32, u0[2] + u1[2], pw); sts32(sd + 320 + 80 + 32, u0[3] + u1[3], pw);
            bar_arrive_p<5, NCONS + 64>(lv);
        }
        {
            const int slot = (ITEM_WD + wg) % NSLOT;
            mbar_wait_p(sbase + SM_WBAR + 8 * (8 + wg), 0, lv);
            const int krow = (lane & 7) + ((lane >> 4) << 3);
            const uint32_t db = sbase + slot * SLOT_BYTES + wl * 2048 + krow * 128;
#pragma unroll
            for (int j = 0; j < 4; j++) ldsm4t(ad[j], db + (((2 * j + ((lane >> 3) & 1)) ^ (krow & 7)) << 4));
            bar_sync_p<6, NCONS + 64>(lv);
            uint32_t b[4];
            ldsm4(b, sa);
#pragma unroll
            for (int j = 0; j < 4; j++) {
                float acc[4] = {0.f, 0.f, 0.f, 0.f};
                mma16816(acc, ad[j], b[0], b[1]);
                st_tag2(p_in2 + (2 * j) * NFCTA * 16, acc[0], acc[1], tag, pw);
                st_tag2(p_in2 + (2 * j + 1) * NFCTA * 16, acc[2], acc[3], tag, pw);
            }
            bar_arrive_p<9, NCONS + 32>(lv);
        }
    }
    if (lv) return;

    {
        const int hw = (tid >> 5) - 9;
        const int red_b = 2 * (c >> 6) + ((lane >> 3) & 1);
        const int red_n = 8 * (c & 63) + 2 * t4 + ((lane >> 4) & 1);
        const float x_res = __bfloat162float(x[red_b * DM + red_n]);
        const int cta0 = (hw * 8 + (c >> 4)) * 4, hh = (c >> 2) & 3;
        const float* q_po = &g_po[(cta0 * 4 + hh) * DH + lane * 4];
        const float* q_pml = &g_pml[(cta0 * 4 + hh) * 2];
        const float* q_in1 = &g_in1[(c * 32 + r) * 16 + 4 * t4];
        float* p_h = &g_h[((lane & 4) ? HREP / 2 : 0) * (NB * DM) + red_b * DM + red_n];
        const float* q_h = &g_h[(c % HREP) * (NB * DM) + hw * DM + lane * 4];
        const float* q_in2 = &g_in2[(c * NFCTA + r) * 16 + 4 * t4];
        __nv_bfloat16* p_out = out + red_b * DM + red_n;
        uint32_t s_ofw = s_of + (hw * 136 + lane * 4) * 2, s_hn = s_xn + hw * 1040 + lane * 8;
        uint32_t s_gu = s_red + (((hw & 1) * 2 + (lane >> 4)) * 20 + (lane & 15)) * 4;
        uint32_t s_actw = s_act + (((hw & 1) * 2 + (lane >> 4)) * 24 + (lane & 15)) * 2;
        pin(q_po); pin(q_pml); pin(q_in1); pin(p_h); pin(q_h); pin(q_in2); pin(p_out); pin(s_ofw); pin(s_hn); pin(s_gu); pin(s_actw);

#pragma unroll 1
        for (int pass = 0; pass < 2; pass++) {
            asm volatile("mov.u32 %0, %1;" : "=r"(lv) : "r"(pass));
            if (lv) {
                if (hw == 0) {
                    uint32_t it = 0;
                    while (true) {
                        const int seen = (int)(ld_rlx1(&g_count) - epoch * NCTA);
                        if (lane == 0) asm volatile("st.volatile.shared.u32 [%0], %1;" ::"r"(sbase + SM_CNT), "r"(seen) : "memory");
                        if (seen >= NCTA) break;
                        __nanosleep(seen > 0 ? 100 : 1000);
                        if (++it > SPIN_LIMIT) __trap();
                    }
                }
                asm volatile("bar.sync 10, 128;" ::: "memory");
                asm volatile("bar.sync 11, 384;" ::: "memory");
                spin_cycles(POLL_DELAY1);
            }
            {
                PollSet<4, 4 * DH, 4, 8> ps;
                poll1(ps, q_po, q_pml, tag, lv);
                const uint4 (&ov)[4] = ps.v;
                const uint2 (&ml)[4] = ps.m;
                const float M = fmaxf(fmaxf(u2f(ml[0].x), u2f(ml[1].x)), fmaxf(u2f(ml[2].x), u2f(ml[3].x)));
                const float e0 = ex2((u2f(ml[0].x) - M) * LOG2E), e1 = ex2((u2f(ml[1].x) - M) * LOG2E);
                const float e2 = ex2((u2f(ml[2].x) - M) * LOG2E), e3 = ex2((u2f(ml[3].x) - M) * LOG2E);
                const float inv = rcp_approx(fmaf(e0, u2f(ml[0].y), e1 * u2f(ml[1].y)) + fmaf(e2, u2f(ml[2].y), e3 * u2f(ml[3].y)));
                const float a0 = fmaf(e0, u2f(ov[0].x), e1 * u2f(ov[1].x)) + fmaf(e2, u2f(ov[2].x), e3 * u2f(ov[3].x));
                const float a1 = fmaf(e0, u2f(ov[0].y), e1 * u2f(ov[1].y)) + fmaf(e2, u2f(ov[2].y), e3 * u2f(ov[3].y));
                const float a2 = fmaf(e0, u2f(ov[0].z), e1 * u2f(ov[1].z)) + fmaf(e2, u2f(ov[2].z), e3 * u2f(ov[3].z));
                const float a3 = fmaf(e0, u2f(ov[0].w), e1 * u2f(ov[1].w)) + fmaf(e2, u2f(ov[2].w), e3 * u2f(ov[3].w));
                sts64(s_ofw, pack_bf16(a0 * inv, a1 * inv), pack_bf16(a2 * inv, a3 * inv), lv);
                bar_arrive_p<3, NALL>(lv);
            }
            float h_res = 0.f;
            if (hw == 3 || !lv) {
                bar_sync_p<8, NCONS + 32>(lv);
                if (lv) spin_cycles(POLL_DELAY);
                const float kk = inbox_reduce<4>(q_in1, tag, lv, lane);
                h_res = bf16r(x_res + bf16r(kk));
#pragma unroll
                for (int rp = 0; rp < HREP / 2; rp++) st_tag1(p_h + rp * (NB * DM), h_res, tag, lv);
                bar_arrive_p<7, 128>(lv);
            }
            if (hw != 3) bar_sync_p<7, 128>(lv);
            if (lv) spin_cycles(POLL_DELAY);
            if (c < NFCTA) {
                PollSet<4, 128, 0, 0> ps;
                poll1(ps, q_h, q_h, tag, lv);
                const uint4 (&u)[4] = ps.v;
                float v[16];
#pragma unroll
                for (int k = 0; k < 4; k++) {
                    v[4 * k + 0] = u2f(u[k].x & 0xffff0000u); v[4 * k + 1] = u2f(u[k].y & 0xffff0000u);
                    v[4 * k + 2] = u2f(u[k].z & 0xffff0000u); v[4 * k + 3] = u2f(u[k].w & 0xffff0000u);
                }
                warp_layernorm_store(v, __shfl_sync(0xffffffffu, v[0], 0), s_hn, lv);
                bar_arrive_p<4, NALL>(lv);
                if (hw < 2 || !lv) {
                    bar_sync_p<5, NCONS + 64>(lv);
                    float gw[8], uw[8];
#pragma unroll
                    for (int w = 0; w < 8; w++) { gw[w] = lds32(s_gu + w * 640); uw[w] = lds32(s_gu + w * 640 + 320); }
                    const float g = bf16r(((gw[0] + gw[1]) + (gw[2] + gw[3])) + ((gw[4] + gw[5]) + (gw[6] + gw[7])));
                    const float u_ = bf16r(((uw[0] + uw[1]) + (uw[2] + uw[3])) + ((uw[4] + uw[5]) + (uw[6] + uw[7])));
                    const float inner = 0.7978845608028654f * fmaf(0.044715f * g * g, g, g);
                    const float ge = bf16r(__fdividef(g, 1.f + __expf(-2.f * inner)));
                    sts16(s_actw, __bfloat16_as_ushort(__float2bfloat16_rn(ge * u_)), lv);
                    bar_arrive_p<6, NCONS + 64>(lv);
                }
            }
            if (hw == 3 || !lv) {
                if (c < NFCTA) bar_sync_p<9, NCONS + 32>(lv);
                if (lv) spin_cycles(POLL_DELAY);
                const float k2 = inbox_reduce<14>(q_in2, tag, lv, lane);
                if (lv && !(lane & 4)) *p_out = __float2bfloat16_rn(h_res + bf16r(k2));
                if (lv && c == 0 && lane == 0) {
                    asm volatile("st.relaxed.gpu.global.u32 [%0], %1;" ::"l"(&g_epoch), "r"(epoch + 1) : "memory");
                }
            }
        }
    }
}

typedef CUresult (*EncodeFn)(CUtensorMap*, CUtensorMapDataType, cuuint32_t, void*, const cuuint64_t*, const cuuint64_t*,
                             const cuuint32_t*, const cuuint32_t*, CUtensorMapInterleave, CUtensorMapSwizzle,
                             CUtensorMapL2promotion, CUtensorMapFloatOOBfill);

CUtensorMap make_map(EncodeFn enc, const void* base, int rank, const cuuint64_t* dims, const cuuint64_t* strides,
                     const cuuint32_t* box, CUtensorMapSwizzle sw, CUtensorMapL2promotion promo) {
    CUtensorMap tm;
    cuuint32_t es[3] = {1, 1, 1};
    enc(&tm, CU_TENSOR_MAP_DATA_TYPE_BFLOAT16, rank, const_cast<void*>(base), dims, strides, box, es,
        CU_TENSOR_MAP_INTERLEAVE_NONE, sw, promo, CU_TENSOR_MAP_FLOAT_OOB_FILL_NONE);
    return tm;
}

}

extern "C" void kernel_launch(void* const* d_in, const int* in_sizes, int n_in, void* d_out, int out_size) {
    (void)in_sizes; (void)n_in; (void)out_size;
    const void* x = d_in[0];
    const void* kc = d_in[1];
    const void* vc = d_in[2];
    const void* wq = d_in[3];
    const void* wo = d_in[4];
    const void* wg = d_in[6];
    const void* wu = d_in[7];
    const void* wd = d_in[8];

    static EncodeFn enc = nullptr;
    if (!enc) {
        void* fn = nullptr;
        cudaDriverEntryPointQueryResult qr;
        cudaGetDriverEntryPoint("cuTensorMapEncodeTiled", &fn, cudaEnableDefault, &qr);
        enc = reinterpret_cast<EncodeFn>(fn);
        cudaFuncSetAttribute(fused_decode_kernel, cudaFuncAttributeMaxDynamicSharedMemorySize, SMEM_BYTES);
    }
    const auto P256 = CU_TENSOR_MAP_L2_PROMOTION_L2_256B;
    CUtensorMap tmK, tmV, tmWq, tmWo, tmWg, tmWu, tmWd;
    {
        cuuint64_t dims[3] = {64, (cuuint64_t)NB * HKV * SK, 2};
        cuuint64_t str[2] = {256, 128};
        cuuint32_t box[3] = {64, 64, 2};
        tmK = make_map(enc, kc, 3, dims, str, box, CU_TENSOR_MAP_SWIZZLE_128B, P256);
        tmV = make_map(enc, vc, 3, dims, str, box, CU_TENSOR_MAP_SWIZZLE_128B, P256);
    }
    {
        cuuint64_t dims[2] = {HQ * DH, DM};
        cuuint64_t str[1] = {HQ * DH * 2};
        cuuint32_t box[2] = {32, 256};
        tmWq = make_map(enc, wq, 2, dims, str, box, CU_TENSOR_MAP_SWIZZLE_64B, P256);
    }
    {
        cuuint64_t dims[3] = {64, HQ * DH, 8};
        cuuint64_t str[2] = {DM * 2, 128};
        cuuint32_t box[3] = {64, 64, 1};
        tmWo = make_map(enc, wo, 3, dims, str, box, CU_TENSOR_MAP_SWIZZLE_128B, P256);
    }
    {
        cuuint64_t dims[2] = {FF, DM};
        cuuint64_t str[1] = {FF * 2};
        cuuint32_t box[2] = {16, 256};
        tmWg = make_map(enc, wg, 2, dims, str, box, CU_TENSOR_MAP_SWIZZLE_32B, P256);
        tmWu = make_map(enc, wu, 2, dims, str, box, CU_TENSOR_MAP_SWIZZLE_32B, P256);
    }
    {
        cuuint64_t dims[3] = {64, FF, 8};
        cuuint64_t str[2] = {DM * 2, 128};
        cuuint32_t box[3] = {64, 16, 4};
        tmWd = make_map(enc, wd, 3, dims, str, box, CU_TENSOR_MAP_SWIZZLE_128B, P256);
    }
    fused_decode_kernel<<<NCTA, NTHREADS, SMEM_BYTES, cudaStreamPerThread>>>(
        tmK, tmV, tmWq, tmWo, tmWg, tmWu, tmWd, (const __nv_bfloat16*)x, (__nv_bfloat16*)d_out);
}
```

```cpp
#include <cuda_runtime.h>
#include <cuda_bf16.h>
#include <cuda.h>
#include <stdint.h>

namespace {

constexpr int NB = 4, DM = 512, HQ = 32, HKV = 8, SK = 8192, DH = 128, FF = 1792;
constexpr int NCTA = 128;
constexpr int NSPLIT = 4;
constexpr int TILE = 128;
constexpr int NTILE = SK / NSPLIT / TILE;
constexpr int SLOT_BYTES = 16384;
constexpr int NSLOT = 12;
constexpr int ITEM_WO = 2 + 4 * NTILE;
constexpr int ITEM_GU = ITEM_WO + 2;
constexpr int ITEM_WD = ITEM_WO + 4;
constexpr int NFCTA = FF / 16;
constexpr int HREP = 4;
constexpr int NCONS = 256;
constexpr int NHELP = 4;
constexpr int NTHREADS = NCONS + 32 + 32 * NHELP;
constexpr int NALL = NCONS + 32 * NHELP;

constexpr int WINDOW = 4;
constexpr int WINDOW_EG = 5;
constexpr int EG_COUNT = 8;
constexpr int WINDOW_T = 4;
constexpr int TRIGGER = 96;
constexpr int POLL_DELAY1 = 300;
constexpr int POLL_DELAY = 450;
constexpr uint32_t SPIN_LIMIT = 1u << 22;

constexpr int SM_MRG = NSLOT * SLOT_BYTES;
constexpr int SM_ML = SM_MRG + 8 * 4 * 136 * 4;
constexpr int SM_XN = SM_ML + 8 * 4 * 2 * 4;
constexpr int SM_QS = SM_XN + 4 * 520 * 2;
constexpr int SM_OF = SM_QS + 4 * 136 * 2;
constexpr int SM_ACT = SM_OF + 4 * 136 * 2;
constexpr int SM_BAR = SM_ACT + 4 * 24 * 2;
constexpr int SM_CNT = SM_BAR + 2 * NSLOT * 8;
constexpr int SM_WBAR = SM_CNT + 16;
constexpr int SM_TOTAL = SM_WBAR + 80;
constexpr int SMEM_BYTES = SM_TOTAL + 1024;

__device__ unsigned g_epoch;
__device__ unsigned g_count;
__device__ __align__(128) float g_q[NB * HQ * DH];
__device__ __align__(128) float g_po[NCTA * 4 * DH];
__device__ __align__(128) float g_pml[NCTA * 4 * 2];
__device__ __align__(128) float g_in1[NCTA * 32 * 16];
__device__ __align__(128) float g_h[HREP * NB * DM];
__device__ __align__(128) float g_in2[NCTA * NFCTA * 16];

__device__ __forceinline__ uint32_t smem_u32(const void* p) { return (uint32_t)__cvta_generic_to_shared(p); }
__device__ __forceinline__ void mbar_init(uint32_t bar, uint32_t cnt) {
    asm volatile("mbarrier.init.shared::cta.b64 [%0], %1;" ::"r"(bar), "r"(cnt) : "memory");
}
__device__ __forceinline__ void mbar_expect_tx(uint32_t bar, uint32_t bytes) {
    asm volatile("mbarrier.arrive.expect_tx.shared::cta.b64 _, [%0], %1;" ::"r"(bar), "r"(bytes) : "memory");
}
__device__ __forceinline__ void mbar_arrive(uint32_t bar) {
    asm volatile("mbarrier.arrive.shared::cta.b64 _, [%0];" ::"r"(bar) : "memory");
}
__device__ __forceinline__ void mbar_wait(uint32_t bar, uint32_t parity) {
    uint32_t done = 0, it = 0;
    while (true) {
        asm volatile("{\n.reg .pred p;\nmbarrier.try_wait.parity.shared::cta.b64 p, [%1], %2;\nselp.u32 %0, 1, 0, p;\n}"
                     : "=r"(done) : "r"(bar), "r"(parity) : "memory");
        if (done) break;
        if (++it > SPIN_LIMIT) __trap();
    }
}
__device__ __forceinline__ void mbar_wait_p(uint32_t bar, uint32_t parity, uint32_t lv) {
    uint32_t it = 0;
    while (true) {
        uint32_t done;
        asm volatile("{\n.reg .pred p, q;\nsetp.ne.u32 q, %3, 0;\nsetp.eq.u32 p, %3, 0;\n"
                     "@q mbarrier.try_wait.parity.shared::cta.b64 p, [%1], %2;\nselp.u32 %0, 1, 0, p;\n}"
                     : "=r"(done) : "r"(bar), "r"(parity), "r"(lv) : "memory");
        if (done) break;
        if (++it > SPIN_LIMIT) __trap();
    }
}
__device__ __forceinline__ void tma2d(uint32_t dst, const CUtensorMap* tm, int c0, int c1, uint32_t bar, uint64_t pol) {
    asm volatile("cp.async.bulk.tensor.2d.shared::cluster.global.mbarrier::complete_tx::bytes.L2::cache_hint [%0], [%1, {%3, %4}], [%2], %5;"
                 ::"r"(dst), "l"(tm), "r"(bar), "r"(c0), "r"(c1), "l"(pol) : "memory");
}
__device__ __forceinline__ void tma3d(uint32_t dst, const CUtensorMap* tm, int c0, int c1, int c2, uint32_t bar, uint64_t pol) {
    asm volatile("cp.async.bulk.tensor.3d.shared::cluster.global.mbarrier::complete_tx::bytes.L2::cache_hint [%0], [%1, {%3, %4, %5}], [%2], %6;"
                 ::"r"(dst), "l"(tm), "r"(bar), "r"(c0), "r"(c1), "r"(c2), "l"(pol) : "memory");
}
__device__ __forceinline__ void tm_prefetch(const CUtensorMap* tm) {
    asm volatile("prefetch.tensormap [%0];" ::"l"(tm) : "memory");
}
__device__ __forceinline__ void ldsm4(uint32_t (&r)[4], uint32_t addr) {
    asm volatile("ldmatrix.sync.aligned.m8n8.x4.shared.b16 {%0,%1,%2,%3}, [%4];"
                 : "=r"(r[0]), "=r"(r[1]), "=r"(r[2]), "=r"(r[3]) : "r"(addr) : "memory");
}
__device__ __forceinline__ void ldsm4t(uint32_t (&r)[4], uint32_t addr) {
    asm volatile("ldmatrix.sync.aligned.m8n8.x4.trans.shared.b16 {%0,%1,%2,%3}, [%4];"
                 : "=r"(r[0]), "=r"(r[1]), "=r"(r[2]), "=r"(r[3]) : "r"(addr) : "memory");
}
__device__ __forceinline__ void mma16816(float (&c)[4], const uint32_t (&a)[4], uint32_t b0, uint32_t b1) {
    asm volatile("mma.sync.aligned.m16n8k16.row.col.f32.bf16.bf16.f32 {%0,%1,%2,%3}, {%4,%5,%6,%7}, {%8,%9}, {%0,%1,%2,%3};"
                 : "+f"(c[0]), "+f"(c[1]), "+f"(c[2]), "+f"(c[3])
                 : "r"(a[0]), "r"(a[1]), "r"(a[2]), "r"(a[3]), "r"(b0), "r"(b1));
}
__device__ __forceinline__ uint32_t movm_t(uint32_t a) {
    uint32_t d;
    asm volatile("movmatrix.sync.aligned.m8n8.trans.b16 %0, %1;" : "=r"(d) : "r"(a));
    return d;
}
__device__ __forceinline__ uint32_t pack_bf16(float lo, float hi) {
    uint32_t d;
    asm("cvt.rn.bf16x2.f32 %0, %1, %2;" : "=r"(d) : "f"(hi), "f"(lo));
    return d;
}
__device__ __forceinline__ float bf16r(float x) { return __bfloat162float(__float2bfloat16_rn(x)); }
__device__ __forceinline__ float bf_lo(uint32_t w) { return __uint_as_float(w << 16); }
__device__ __forceinline__ float bf_hi(uint32_t w) { return __uint_as_float(w & 0xffff0000u); }
__device__ __forceinline__ float ex2(float x) {
    float y;
    asm("ex2.approx.ftz.f32 %0, %1;" : "=f"(y) : "f"(x));
    return y;
}
__device__ __forceinline__ void cons_sync() { asm volatile("bar.sync 1, 256;" ::: "memory"); }
template <int ID, int CNT> __device__ __forceinline__ void bar_sync_p(uint32_t lv) {
    asm volatile("{\n.reg .pred q;\nsetp.ne.u32 q, %0, 0;\n@q bar.sync %1, %2;\n}" ::"r"(lv), "n"(ID), "n"(CNT) : "memory");
}
template <int ID, int CNT> __device__ __forceinline__ void bar_arrive_p(uint32_t lv) {
    asm volatile("{\n.reg .pred q;\nsetp.ne.u32 q, %0, 0;\n@q bar.arrive %1, %2;\n}" ::"r"(lv), "n"(ID), "n"(CNT) : "memory");
}
__device__ __forceinline__ void spin_cycles(uint32_t n) {
    const uint32_t t0 = (uint32_t)clock();
    while ((uint32_t)clock() - t0 < n) {}
}
__device__ __forceinline__ void sts32(uint32_t a, float v, uint32_t p) {
    asm volatile("{\n.reg .pred q;\nsetp.ne.u32 q, %2, 0;\n@q st.shared.f32 [%0], %1;\n}" ::"r"(a), "f"(v), "r"(p) : "memory");
}
__device__ __forceinline__ void sts16(uint32_t a, uint16_t v, uint32_t p) {
    asm volatile("{\n.reg .pred q;\nsetp.ne.u32 q, %2, 0;\n@q st.shared.u16 [%0], %1;\n}" ::"r"(a), "h"(v), "r"(p) : "memory");
}
__device__ __forceinline__ void sts64(uint32_t a, uint32_t x, uint32_t y, uint32_t p) {
    asm volatile("{\n.reg .pred q;\nsetp.ne.u32 q, %3, 0;\n@q st.shared.v2.u32 [%0], {%1, %2};\n}" ::"r"(a), "r"(x), "r"(y), "r"(p) : "memory");
}
__device__ __forceinline__ float lds32(uint32_t a) {
    float v; asm volatile("ld.shared.f32 %0, [%1];" : "=f"(v) : "r"(a) : "memory"); return v;
}
__device__ __forceinline__ float2 lds64(uint32_t a) {
    float2 v; asm volatile("ld.shared.v2.f32 {%0, %1}, [%2];" : "=f"(v.x), "=f"(v.y) : "r"(a) : "memory"); return v;
}

__device__ __forceinline__ float u2f(uint32_t u) { return __uint_as_float(u); }
__device__ __forceinline__ float tagf(float v, uint32_t tag) { return __uint_as_float((__float_as_uint(v) & ~1u) | tag); }
__device__ __forceinline__ void st_tag1(float* ptr, float v, uint32_t tag, uint32_t p) {
    asm volatile("{\n.reg .pred q;\nsetp.ne.u32 q, %2, 0;\n@q st.relaxed.gpu.global.f32 [%0], %1;\n}"
                 ::"l"(ptr), "f"(tagf(v, tag)), "r"(p) : "memory");
}
__device__ __forceinline__ void st_tag2(float* ptr, float a, float b, uint32_t tag, uint32_t p) {
    asm volatile("{\n.reg .pred q;\nsetp.ne.u32 q, %3, 0;\n@q st.relaxed.gpu.global.v2.f32 [%0], {%1, %2};\n}"
                 ::"l"(ptr), "f"(tagf(a, tag)), "f"(tagf(b, tag)), "r"(p) : "memory");
}
__device__ __forceinline__ void ld_rlx4(uint4& v, const float* ptr, uint32_t p) {
    asm volatile("{\n.reg .pred q;\nsetp.ne.u32 q, %5, 0;\n@q ld.relaxed.gpu.global.v4.u32 {%0,%1,%2,%3}, [%4];\n}"
                 : "+r"(v.x), "+r"(v.y), "+r"(v.z), "+r"(v.w) : "l"(ptr), "r"(p) : "memory");
}
__device__ __forceinline__ void ld_rlx2(uint2& v, const float* ptr, uint32_t p) {
    asm volatile("{\n.reg .pred q;\nsetp.ne.u32 q, %3, 0;\n@q ld.relaxed.gpu.global.v2.u32 {%0,%1}, [%2];\n}"
                 : "+r"(v.x), "+r"(v.y) : "l"(ptr), "r"(p) : "memory");
}
__device__ __forceinline__ uint32_t ld_rlx1(const unsigned* p) {
    uint32_t v;
    asm volatile("ld.relaxed.gpu.global.u32 %0, [%1];" : "=r"(v) : "l"(p) : "memory");
    return v;
}
__device__ __forceinline__ uint32_t bad4(const uint4& v, uint32_t tag) {
    uint32_t u, w, r;
    asm("lop3.b32 %0, %1, %2, %3, 0x7E;" : "=r"(u) : "r"(v.x), "r"(v.y), "r"(tag));
    asm("lop3.b32 %0, %1, %2, %3, 0x7E;" : "=r"(w) : "r"(v.z), "r"(v.w), "r"(tag));
    asm("lop3.b32 %0, %1, %2, 1, 0xA8;" : "=r"(r) : "r"(u), "r"(w));
    return r;
}
__device__ __forceinline__ uint32_t bad2(const uint2& v, uint32_t tag) {
    uint32_t u;
    asm("lop3.b32 %0, %1, %2, %3, 0x7E;" : "=r"(u) : "r"(v.x), "r"(v.y), "r"(tag));
    return u & 1u;
}
template <typename T> __device__ __forceinline__ void pin(T*& p) { asm volatile("" : "+l"(p)); }
__device__ __forceinline__ void pin(uint32_t& v) { asm volatile("" : "+r"(v)); }
__device__ __forceinline__ float sqrt_approx(float x) { float y; asm("sqrt.approx.ftz.f32 %0, %1;" : "=f"(y) : "f"(x)); return y; }
__device__ __forceinline__ float rcp_approx(float x) { float y; asm("rcp.approx.ftz.f32 %0, %1;" : "=f"(y) : "f"(x)); return y; }
template <int NK, int KS, int NM, int MS>
struct PollSet {
    uint4 v[NK]; uint2 m[NM > 0 ? NM : 1]; uint32_t bad[NK], badm[NM > 0 ? NM : 1];
    __device__ __forceinline__ void init(uint32_t tag, uint32_t lv) {
#pragma unroll
        for (int k = 0; k < NK; k++) { v[k] = make_uint4(tag, tag, tag, tag); bad[k] = lv; }
#pragma unroll
        for (int k = 0; k < NM; k++) { m[k] = make_uint2(tag, tag); badm[k] = lv; }
    }
    __device__ __forceinline__ void issue(const float* src, const float* src2) {
#pragma unroll
        for (int k = 0; k < NK; k++) ld_rlx4(v[k], src + k * KS, bad[k]);
#pragma unroll
        for (int k = 0; k < NM; k++) ld_rlx2(m[k], src2 + k * MS, badm[k]);
    }
    __device__ __forceinline__ bool complete(uint32_t tag) {
        uint32_t any = 0;
#pragma unroll
        for (int k = 0; k < NK; k++) { bad[k] = bad4(v[k], tag); any |= bad[k]; }
#pragma unroll
        for (int k = 0; k < NM; k++) { badm[k] = bad2(m[k], tag); any |= badm[k]; }
        return !__any_sync(0xffffffffu, any);
    }
};
constexpr float LOG2E = 1.4426950408889634f;

__device__ __forceinline__ void warp_layernorm_store(const float (&v)[16], float c, uint32_t dst, uint32_t p) {
    float s1[4], s2[4];
#pragma unroll
    for (int k = 0; k < 4; k++) {
        const float d0 = v[4 * k] - c, d1 = v[4 * k + 1] - c, d2 = v[4 * k + 2] - c, d3 = v[4 * k + 3] - c;
        s1[k] = (d0 + d1) + (d2 + d3);
        s2[k] = fmaf(d0, d0, d1 * d1) + fmaf(d2, d2, d3 * d3);
    }
    float t1 = (s1[0] + s1[1]) + (s1[2] + s1[3]), t2 = (s2[0] + s2[1]) + (s2[2] + s2[3]);
#pragma unroll
    for (int o = 16; o > 0; o >>= 1) {
        t1 += __shfl_xor_sync(0xffffffffu, t1, o);
        t2 += __shfl_xor_sync(0xffffffffu, t2, o);
    }
    const float md = t1 * (1.f / 512.f);
    const float mean = bf16r(c + md);
    const float var = bf16r(fmaxf(fmaf(-md, md, t2 * (1.f / 512.f)), 0.f));
    const float inv = rcp_approx(bf16r(sqrt_approx(bf16r(var + 1e-5f))));
#pragma unroll
    for (int k = 0; k < 4; k++) {
        const uint32_t t01 = pack_bf16(v[4 * k + 0] - mean, v[4 * k + 1] - mean);
        const uint32_t t23 = pack_bf16(v[4 * k + 2] - mean, v[4 * k + 3] - mean);
        sts64(dst + k * 256, pack_bf16(bf_lo(t01) * inv, bf_hi(t01) * inv), pack_bf16(bf_lo(t23) * inv, bf_hi(t23) * inv), p);
    }
}

template <class PS>
__device__ __forceinline__ void poll1(PS& ps, const float* src, const float* src2, uint32_t tag, uint32_t lv) {
    ps.init(tag, lv);
    uint32_t it = 0;
    while (true) {
        ps.issue(src, src2);
        if (ps.complete(tag)) break;
        if (++it > SPIN_LIMIT) __trap();
    }
}
template <bool PART>
__device__ __forceinline__ float inbox_reduce(const float* src, uint32_t tag, uint32_t lv, int lane) {
    PollSet<4, 128, 0, 0> ps;
    ps.init(tag, lv);
    const bool last = !PART || (lane >> 2) < 4;
    if (!last) ps.bad[3] = 0;
    uint32_t it = 0;
    while (true) {
        ps.issue(src, src);
        if (ps.complete(tag)) break;
        if (++it > SPIN_LIMIT) __trap();
    }
    const float m3 = last ? 1.f : 0.f;
    const float a = (u2f(ps.v[0].x) + u2f(ps.v[1].x)) + fmaf(m3, u2f(ps.v[3].x), u2f(ps.v[2].x));
    const float b = (u2f(ps.v[0].y) + u2f(ps.v[1].y)) + fmaf(m3, u2f(ps.v[3].y), u2f(ps.v[2].y));
    const float c = (u2f(ps.v[0].z) + u2f(ps.v[1].z)) + fmaf(m3, u2f(ps.v[3].z), u2f(ps.v[2].z));
    const float d = (u2f(ps.v[0].w) + u2f(ps.v[1].w)) + fmaf(m3, u2f(ps.v[3].w), u2f(ps.v[2].w));
    const bool hi = lane & 16, h2 = lane & 8;
    float k0 = hi ? c : a, k1 = hi ? d : b;
    k0 += __shfl_xor_sync(0xffffffffu, hi ? a : c, 16);
    k1 += __shfl_xor_sync(0xffffffffu, hi ? b : d, 16);
    float kk = h2 ? k1 : k0;
    kk += __shfl_xor_sync(0xffffffffu, h2 ? k0 : k1, 8);
    kk += __shfl_xor_sync(0xffffffffu, kk, 4);
    return kk;
}


__global__ void __launch_bounds__(NTHREADS, 1)
fused_decode_kernel(const __grid_constant__ CUtensorMap tmK, const __grid_constant__ CUtensorMap tmV,
                    const __grid_constant__ CUtensorMap tmWq, const __grid_constant__ CUtensorMap tmWo,
                    const __grid_constant__ CUtensorMap tmWg, const __grid_constant__ CUtensorMap tmWu,
                    const __grid_constant__ CUtensorMap tmWd,
                    const __nv_bfloat16* __restrict__ x, __nv_bfloat16* __restrict__ out) {
    extern __shared__ uint8_t smem_raw[];
    const uint32_t sbase = (smem_u32(smem_raw) + 1023u) & ~1023u;
    const uint32_t bar_full = sbase + SM_BAR, bar_empty = bar_full + NSLOT * 8;
    const int tid = threadIdx.x, lane = tid & 31;
    const int c = blockIdx.x;
    const int row0 = (c >> 2) * SK + (c & 3) * (SK / NSPLIT);
    uint64_t pol_stream = 0;
    if (tid == NCONS) {
        tm_prefetch(&tmWq); tm_prefetch(&tmK); tm_prefetch(&tmV);
        for (int i = 0; i < 4; i++) mbar_init(bar_full + 8 * i, 1);
        asm volatile("fence.proxy.async.shared::cta;" ::: "memory");
        asm volatile("createpolicy.fractional.L2::evict_first.b64 %0, 1.0;" : "=l"(pol_stream));
        mbar_expect_tx(bar_full, SLOT_BYTES);
        tma2d(sbase, &tmWq, 32 * c, 0, bar_full, pol_stream);
        mbar_expect_tx(bar_full + 8, SLOT_BYTES);
        tma2d(sbase + SLOT_BYTES, &tmWq, 32 * c, 256, bar_full + 8, pol_stream);
        mbar_expect_tx(bar_full + 16, SLOT_BYTES);
        tma3d(sbase + 2 * SLOT_BYTES, &tmK, 0, row0, 0, bar_full + 16, pol_stream);
        mbar_expect_tx(bar_full + 24, SLOT_BYTES);
        tma3d(sbase + 3 * SLOT_BYTES, &tmK, 0, row0 + 64, 0, bar_full + 24, pol_stream);
        for (int i = 4; i < NSLOT; i++) mbar_init(bar_full + 8 * i, 1);
        for (int i = 0; i < NSLOT; i++) mbar_init(bar_empty + 8 * i, 4);
        for (int i = 0; i < 10; i++) mbar_init(sbase + SM_WBAR + 8 * i, 1);
        asm volatile("fence.proxy.async.shared::cta;" ::: "memory");
        asm volatile("st.volatile.shared.u32 [%0], %1;" ::"r"(sbase + SM_CNT), "r"(0) : "memory");
    }
    __syncthreads();

    if ((tid >> 5) == 8) {
        if (lane == 0) {
            auto acquire = [&](int i, int window) {
                if (i >= NSLOT) mbar_wait(bar_empty + 8 * (i % NSLOT), ((i / NSLOT) - 1) & 1);
                if (i >= window) { const int j = i - window; mbar_wait(bar_full + 8 * (j % NSLOT), (j / NSLOT) & 1); }
            };
            auto seen_count = [&]() {
                uint32_t seen;
                asm volatile("ld.volatile.shared.u32 %0, [%1];" : "=r"(seen) : "r"(sbase + SM_CNT) : "memory");
                return (int)seen;
            };
#pragma unroll 1
            for (int i = 4; i < ITEM_WO; i++) {
                const int slot = i % NSLOT;
                acquire(i, (i >= ITEM_WO - 24 && seen_count() >= EG_COUNT) ? WINDOW_EG : WINDOW);
                const int t = (i - 2) >> 2, sub = (i - 2) & 3;
                mbar_expect_tx(bar_full + 8 * slot, SLOT_BYTES);
                tma3d(sbase + slot * SLOT_BYTES, (sub & 2) ? &tmV : &tmK, 0, row0 + t * TILE + (sub & 1) * 64, 0,
                      bar_full + 8 * slot, pol_stream);
            }
            asm volatile("red.relaxed.gpu.global.add.u32 [%0], 1;" ::"l"(&g_count) : "memory");
            {
                uint32_t it = 0;
                while (seen_count() < TRIGGER) {
                    __nanosleep(20);
                    if (++it > SPIN_LIMIT) __trap();
                }
            }
            const int npiece = (c < NFCTA) ? 10 : 4;
#pragma unroll 1
            for (int j = 0; j < npiece; j++) {
                const int item = j < 4 ? ITEM_WO + (j >> 1) : (j < 8 ? ITEM_GU + ((j - 4) >> 1) : ITEM_WD + (j - 8));
                const int slot = item % NSLOT;
                mbar_wait(bar_empty + 8 * slot, ((item / NSLOT) - 1) & 1);
                if (j >= WINDOW_T) mbar_wait(sbase + SM_WBAR + 8 * (j - WINDOW_T), 0);
                else if (j < 2) { const int jj = ITEM_WO - 2 + j; mbar_wait(bar_full + 8 * (jj % NSLOT), (jj / NSLOT) & 1); }
                const uint32_t fb = sbase + SM_WBAR + 8 * j, dst = sbase + slot * SLOT_BYTES + ((j < 8) ? (j & 1) * 8192 : 0);
                mbar_expect_tx(fb, 8192);
                if (j < 4) tma3d(dst, &tmWo, 0, 128 * (c >> 2) + 64 * (j & 1), 2 * (c & 3) + (j >> 1), fb, pol_stream);
                else if (j < 8) tma2d(dst, (j & 1) ? &tmWu : &tmWg, 16 * c, 256 * ((j - 4) >> 1), fb, pol_stream);
                else tma3d(dst, &tmWd, 0, 16 * c, 4 * (j - 8), fb, pol_stream);
            }
        }
        return;
    }

    uint32_t lv;
    asm volatile("mov.u32 %0, %1;" : "=r"(lv) : "r"((tid < NCONS) ? 1u : 0u));
    const int warp = lv ? (tid >> 5) : 0;
    const int vtid = warp * 32 + lane;
    const int r = lane >> 2, t4 = lane & 3;
    const int wg = warp >> 2, wl = warp & 3;
    const uint32_t s_red = sbase + SM_MRG, s_ml = sbase + SM_ML, s_xn = sbase + SM_XN;
    const uint32_t s_qs = sbase + SM_QS, s_of = sbase + SM_OF, s_act = sbase + SM_ACT;
    const int brow = lane & 3, bch = lane >> 3;

    uint2 xw[4];
#pragma unroll
    for (int k = 0; k < 4; k++) {
        xw[k] = make_uint2(0u, 0u);
        asm volatile("{\n.reg .pred q;\nsetp.ne.u32 q, %3, 0;\n@q ld.global.nc.v2.u32 {%0, %1}, [%2];\n}"
                     : "+r"(xw[k].x), "+r"(xw[k].y) : "l"(x + (warp & 3) * DM + k * 128 + lane * 4), "r"((uint32_t)(lv && warp < NB)));
    }
    const unsigned epoch = ld_rlx1(&g_epoch);
    uint32_t tag = 0;

    float* p_po = &g_po[(c * 4 + (vtid >> 6)) * DH + (vtid & 63) * 2];
    float* p_pml = &g_pml[(c * 4 + (vtid >> 6)) * 2];
    float* p_in1 = &g_in1[((t4 * 64 + 16 * (c & 3) + 2 * warp) * 32 + (c >> 2)) * 16 + 2 * r];
    float* p_in2 = &g_in2[((t4 * 64 + 8 * warp) * NFCTA + (c < NFCTA ? c : 0)) * 16 + 2 * r];
    pin(p_po); pin(p_pml); pin(p_in1); pin(p_in2);

    float o[8][4];
#pragma unroll
    for (int j = 0; j < 8; j++) { o[j][0] = o[j][1] = o[j][2] = o[j][3] = 0.f; }
    float mfin0 = 0.f, mfin1 = 0.f;

    if (lv) {
        if (warp < NB) {
            float v[16];
#pragma unroll
            for (int k = 0; k < 4; k++) {
                const uint2 w = xw[k];
                v[4 * k + 0] = bf_lo(w.x); v[4 * k + 1] = bf_hi(w.x); v[4 * k + 2] = bf_lo(w.y); v[4 * k + 3] = bf_hi(w.y);
            }
            warp_layernorm_store(v, __shfl_sync(0xffffffffu, v[0], 0), s_xn + warp * 1040 + lane * 8, 1u);
        }
        cons_sync();
        asm volatile("lop3.b32 %0, %1, 1, 1, 0x6A;" : "=r"(tag) : "r"(epoch));

        mbar_wait(bar_full + 8 * wg, 0);
        {
            float acc[2][4] = {};
#pragma unroll
            for (int kp = 0; kp < 2; kp++) {
                uint32_t b[4];
                ldsm4(b, s_xn + brow * 1040 + (warp * 64 + kp * 32 + bch * 8) * 2);
#pragma unroll
                for (int k2 = 0; k2 < 2; k2++) {
                    const int krow = warp * 64 + kp * 32 + k2 * 16 + (lane & 7) + ((lane >> 4) << 3);
#pragma unroll
                    for (int mt = 0; mt < 2; mt++) {
                        const int chunk = mt * 2 + ((lane >> 3) & 1);
                        uint32_t a[4];
                        ldsm4t(a, sbase + krow * 64 + ((chunk ^ ((krow >> 1) & 3)) << 4));
                        mma16816(acc[mt], a, b[2 * k2], b[2 * k2 + 1]);
                    }
                }
            }
            __syncwarp();
            if (lane == 0) mbar_arrive(bar_empty + 8 * wg);
            const uint32_t pq = t4 < 2;
#pragma unroll
            for (int mt = 0; mt < 2; mt++) {
                const uint32_t dst = s_red + (warp * 144 + (2 * t4) * 36 + mt * 16 + r) * 4;
                sts32(dst, acc[mt][0], pq); sts32(dst + 144, acc[mt][1], pq);
                sts32(dst + 32, acc[mt][2], pq); sts32(dst + 144 + 32, acc[mt][3], pq);
            }
            cons_sync();
            if (tid < 128) {
                float s = 0.f;
#pragma unroll
                for (int w = 0; w < 8; w++) s += lds32(s_red + (w * 144 + warp * 36 + lane) * 4);
                st_tag1(&g_q[warp * (HQ * DH) + 32 * c + lane], bf16r(s), tag, 1u);
                const int g = c >> 2;
                const float* src = &g_q[(g >> 3) * (HQ * DH) + (g & 7) * 512 + tid * 4];
                uint4 v;
                uint32_t it = 0;
                while (true) {
                    ld_rlx4(v, src, 1u);
                    if (!(bad4(v, tag) & 1)) break;
                    if (++it > SPIN_LIMIT) __trap();
                }
                sts64(s_qs + (warp * 136 + lane * 4) * 2, (v.x >> 16) | (v.y & 0xffff0000u), (v.z >> 16) | (v.w & 0xffff0000u), 1u);
            }
            cons_sync();
        }

        uint32_t qf[8][2];
#pragma unroll
        for (int j = 0; j < 8; j += 2) {
            uint32_t b[4];
            ldsm4(b, s_qs + brow * 272 + (j * 16 + bch * 8) * 2);
            qf[j][0] = b[0]; qf[j][1] = b[1]; qf[j + 1][0] = b[2]; qf[j + 1][1] = b[3];
        }
        const int krow = wl * 16 + (lane & 7) + (((lane >> 3) & 1) << 3);
        const int kch = lane >> 4;
        const int vrow = wl * 16 + (lane & 7) + ((lane >> 4) << 3);
        const int vch = (lane >> 3) & 1;
        const float scale = 0.08838834764831845f;
        float m0 = -INFINITY, m1 = -INFINITY, l0 = 0.f, l1 = 0.f;

#pragma unroll 1
        for (int t = 0; t < NTILE; t++) {
            const int ik = 2 + 4 * t + wg, iv = ik + 2;
            const int sk = ik % NSLOT, sv = iv % NSLOT;
            mbar_wait(bar_full + 8 * sk, (ik / NSLOT) & 1);
            float sa[4] = {0.f, 0.f, 0.f, 0.f}, sb[4] = {0.f, 0.f, 0.f, 0.f};
            const uint32_t kb = sbase + sk * SLOT_BYTES + krow * 128;
#pragma unroll
            for (int j = 0; j < 8; j += 2) {
                uint32_t a0[4], a1[4];
                ldsm4(a0, kb + (j >> 2) * 8192 + (((((j & 3) << 1) + kch) ^ (krow & 7)) << 4));
                ldsm4(a1, kb + ((j + 1) >> 2) * 8192 + ((((((j + 1) & 3) << 1) + kch) ^ (krow & 7)) << 4));
                mma16816(sa, a0, qf[j][0], qf[j][1]);
                mma16816(sb, a1, qf[j + 1][0], qf[j + 1][1]);
            }
            __syncwarp();
            if (lane == 0) mbar_arrive(bar_empty + 8 * sk);
            const float s0 = bf16r(bf16r(sa[0] + sb[0]) * scale), s1 = bf16r(bf16r(sa[1] + sb[1]) * scale);
            const float s2 = bf16r(bf16r(sa[2] + sb[2]) * scale), s3 = bf16r(bf16r(sa[3] + sb[3]) * scale);
            float x0 = fmaxf(fmaxf(s0, s2), m0), x1 = fmaxf(fmaxf(s1, s3), m1);
#pragma unroll
            for (int off = 4; off < 32; off <<= 1) {
                x0 = fmaxf(x0, __shfl_xor_sync(0xffffffffu, x0, off));
                x1 = fmaxf(x1, __shfl_xor_sync(0xffffffffu, x1, off));
            }
            if (t == NTILE - 1) {
                if (r == 0 && t4 < 2) asm volatile("st.shared.v2.f32 [%0], {%1, %2};" ::"r"(s_ml + (warp * 4 + t4 * 2) * 4), "f"(x0), "f"(x1) : "memory");
                cons_sync();
#pragma unroll
                for (int w = 0; w < 8; w++) {
                    const float2 mw = lds64(s_ml + (w * 4 + (t4 & 1) * 2) * 4);
                    x0 = fmaxf(x0, mw.x); x1 = fmaxf(x1, mw.y);
                }
            }
            if (__any_sync(0xffffffffu, (x0 > m0) || (x1 > m1))) {
                const float a0 = ex2((m0 - x0) * LOG2E), a1 = ex2((m1 - x1) * LOG2E);
                m0 = x0; m1 = x1;
                l0 *= a0; l1 *= a1;
#pragma unroll
                for (int j = 0; j < 8; j++) { o[j][0] *= a0; o[j][1] *= a1; o[j][2] *= a0; o[j][3] *= a1; }
            }
            const float p0 = ex2((s0 - m0) * LOG2E), p1 = ex2((s1 - m1) * LOG2E);
            const float p2 = ex2((s2 - m0) * LOG2E), p3 = ex2((s3 - m1) * LOG2E);
            l0 += p0 + p2; l1 += p1 + p3;
            const uint32_t pb0 = movm_t(pack_bf16(p0, p1));
            const uint32_t pb1 = movm_t(pack_bf16(p2, p3));
            if (t == NTILE - 1) {
#pragma unroll
                for (int off = 4; off < 32; off <<= 1) {
                    l0 += __shfl_xor_sync(0xffffffffu, l0, off);
                    l1 += __shfl_xor_sync(0xffffffffu, l1, off);
                }
                if (r == 0 && t4 < 2) asm volatile("st.shared.v2.f32 [%0], {%1, %2};" ::"r"(s_ml + 128 + (warp * 4 + t4 * 2) * 4), "f"(l0), "f"(l1) : "memory");
            }

            mbar_wait(bar_full + 8 * sv, (iv / NSLOT) & 1);
            const uint32_t vb = sbase + sv * SLOT_BYTES + vrow * 128;
#pragma unroll
            for (int j = 0; j < 8; j++) {
                uint32_t a[4];
                ldsm4t(a, vb + (j >> 2) * 8192 + (((((j & 3) << 1) + vch) ^ (vrow & 7)) << 4));
                mma16816(o[j], a, pb0, pb1);
            }
            __syncwarp();
            if (lane == 0) mbar_arrive(bar_empty + 8 * sv);
        }
        mfin0 = m0; mfin1 = m1;
    } else {
        tag = (epoch & 1u) ^ 1u;
        __nanosleep(6000);
        const int wt = tid - (NCONS + 32);
        const float z = __uint_as_float(tag ^ 1u);
        auto st4 = [&](float* p) {
            asm volatile("st.relaxed.gpu.global.v4.f32 [%0], {%1, %1, %1, %1};" ::"l"(p), "f"(z) : "memory");
        };
        st4(&g_po[c * 512 + wt * 4]);
        st4(&g_in1[((((wt >> 2) >> 4) * 64 + 16 * (c & 3) + ((wt >> 2) & 15)) * 32 + (c >> 2)) * 16 + (wt & 3) * 4]);
        if (c < NFCTA)
            for (int i = wt; i < 512; i += 128) st4(&g_in2[((i >> 2) * NFCTA + c) * 16 + (i & 3) * 4]);
        if (wt < 16) st4(&g_h[(wt >> 2) * (NB * DM) + (2 * (c >> 6) + ((wt >> 1) & 1)) * DM + 8 * (c & 63) + (wt & 1) * 4]);
        else if (wt < 18) st4(&g_pml[c * 8 + (wt - 16) * 4]);
        asm volatile("bar.arrive 2, %0;" ::"n"(NALL) : "memory");
    }

    const uint32_t pw = lv && (t4 < 2);
    {
        const uint32_t dst = s_red + (warp * 544 + (2 * t4) * 136 + r) * 4;
#pragma unroll
        for (int j = 0; j < 8; j++) {
            sts32(dst + j * 64, o[j][0], pw);
            sts32(dst + 544 + j * 64, o[j][1], pw);
            sts32(dst + j * 64 + 32, o[j][2], pw);
            sts32(dst + 544 + j * 64 + 32, o[j][3], pw);
        }
        const int h = vtid >> 6;
        const uint32_t src = s_red + (h * 136 + (vtid & 63) * 2) * 4;
        const float Mh = __shfl_sync(0xffffffffu, (h & 1) ? mfin1 : mfin0, h >> 1);
        bar_sync_p<2, NALL>(lv);
        float2 ov[8]; float lw[8];
#pragma unroll
        for (int w = 0; w < 8; w++) { ov[w] = lds64(src + w * 2176); lw[w] = lds32(s_ml + 128 + (w * 4 + h) * 4); }
        const float a0 = ((ov[0].x + ov[1].x) + (ov[2].x + ov[3].x)) + ((ov[4].x + ov[5].x) + (ov[6].x + ov[7].x));
        const float a1 = ((ov[0].y + ov[1].y) + (ov[2].y + ov[3].y)) + ((ov[4].y + ov[5].y) + (ov[6].y + ov[7].y));
        const float L = ((lw[0] + lw[1]) + (lw[2] + lw[3])) + ((lw[4] + lw[5]) + (lw[6] + lw[7]));
        st_tag2(p_po, a0, a1, tag, lv);
        st_tag2(p_pml, Mh, L, tag, lv && (vtid & 63) == 0);
        bar_arrive_p<11, NALL>(lv);
    }
    {
        const int slot = (ITEM_WO + wg) % NSLOT;
        mbar_wait_p(sbase + SM_WBAR + 8 * (2 * wg), 0, lv);
        mbar_wait_p(sbase + SM_WBAR + 8 * (2 * wg + 1), 0, lv);
        const int krow = (lane & 7) + ((lane >> 4) << 3);
        const uint32_t wb = sbase + slot * SLOT_BYTES + krow * 128 + ((((wl << 1) + ((lane >> 3) & 1)) ^ (krow & 7)) << 4);
        uint32_t a[8][4];
#pragma unroll
        for (int ks = 0; ks < 8; ks++) ldsm4t(a[ks], wb + ks * 2048);
        uint32_t sb = s_of + brow * 272 + bch * 16;
        pin(sb);
        bar_sync_p<3, NALL>(lv);
        uint32_t b[4][4];
#pragma unroll
        for (int kp = 0; kp < 4; kp++) ldsm4(b[kp], sb + kp * 64);
        float acc[4][4] = {};
#pragma unroll
        for (int kp = 0; kp < 4; kp++) {
            mma16816(acc[kp], a[2 * kp], b[kp][0], b[kp][1]);
            mma16816(acc[kp], a[2 * kp + 1], b[kp][2], b[kp][3]);
        }
        st_tag2(p_in1, (acc[0][0] + acc[1][0]) + (acc[2][0] + acc[3][0]), (acc[0][1] + acc[1][1]) + (acc[2][1] + acc[3][1]), tag, pw);
        st_tag2(p_in1 + 32 * 16, (acc[0][2] + acc[1][2]) + (acc[2][2] + acc[3][2]), (acc[0][3] + acc[1][3]) + (acc[2][3] + acc[3][3]), tag, pw);
        bar_arrive_p<8, NCONS + 32>(lv);
    }
    if (c < NFCTA) {
        uint32_t ag[4][4], au[4][4], ad[4][4];
        {
            const int slot = (ITEM_GU + wg) % NSLOT;
            mbar_wait_p(sbase + SM_WBAR + 8 * (4 + 2 * wg), 0, lv);
            mbar_wait_p(sbase + SM_WBAR + 8 * (5 + 2 * wg), 0, lv);
            const int krow = wl * 64 + (lane & 7) + ((lane >> 4) << 3);
            const uint32_t gb = sbase + slot * SLOT_BYTES + krow * 32 + ((((lane >> 3) & 1) ^ ((krow >> 2) & 1)) << 4);
#pragma unroll
            for (int ks = 0; ks < 4; ks++) { ldsm4t(ag[ks], gb + ks * 512); ldsm4t(au[ks], gb + 8192 + ks * 512); }
        }
        uint32_t sb = s_xn + brow * 1040 + (warp * 64 + bch * 8) * 2;
        uint32_t sd = s_red + (warp * 160 + (2 * t4) * 20 + r) * 4;
        uint32_t sa = s_act + brow * 48 + (bch & 1) * 16;
        pin(sb); pin(sd); pin(sa);
        bar_sync_p<4, NALL>(lv);
        {
            uint32_t b0[4], b1[4];
            ldsm4(b0, sb); ldsm4(b1, sb + 64);
            float g0[4] = {}, g1[4] = {}, u0[4] = {}, u1[4] = {};
            mma16816(g0, ag[0], b0[0], b0[1]); mma16816(u0, au[0], b0[0], b0[1]);
            mma16816(g1, ag[2], b1[0], b1[1]); mma16816(u1, au[2], b1[0], b1[1]);
            mma16816(g0, ag[1], b0[2], b0[3]); mma16816(u0, au[1], b0[2], b0[3]);
            mma16816(g1, ag[3], b1[2], b1[3]); mma16816(u1, au[3], b1[2], b1[3]);
            sts32(sd, g0[0] + g1[0], pw);        sts32(sd + 80, g0[1] + g1[1], pw);
            sts32(sd + 32, g0[2] + g1[2], pw);   sts32(sd + 80 + 32, g0[3] + g1[3], pw);
            sts32(sd + 320, u0[0] + u1[0], pw);      sts32(sd + 320 + 80, u0[1] + u1[1], pw);
            sts32(sd + 320 + 32, u0[2] + u1[2], pw); sts32(sd + 320 + 80 + 32, u0[3] + u1[3], pw);
            bar_arrive_p<5, NCONS + 64>(lv);
        }
        {
            const int slot = (ITEM_WD + wg) % NSLOT;
            mbar_wait_p(sbase + SM_WBAR + 8 * (8 + wg), 0, lv);
            const int krow = (lane & 7) + ((lane >> 4) << 3);
            const uint32_t db = sbase + slot * SLOT_BYTES + wl * 2048 + krow * 128;
#pragma unroll
            for (int j = 0; j < 4; j++) ldsm4t(ad[j], db + (((2 * j + ((lane >> 3) & 1)) ^ (krow & 7)) << 4));
            bar_sync_p<6, NCONS + 64>(lv);
            uint32_t b[4];
            ldsm4(b, sa);
#pragma unroll
            for (int j = 0; j < 4; j++) {
                float acc[4] = {0.f, 0.f, 0.f, 0.f};
                mma16816(acc, ad[j], b[0], b[1]);
                st_tag2(p_in2 + (2 * j) * NFCTA * 16, acc[0], acc[1], tag, pw);
                st_tag2(p_in2 + (2 * j + 1) * NFCTA * 16, acc[2], acc[3], tag, pw);
            }
            bar_arrive_p<9, NALL>(lv);
        }
    }
    if (lv) return;

    {
        const int hw = (tid >> 5) - 9;
        const int red_b = 2 * (c >> 6) + ((lane >> 3) & 1);
        const int red_n = 8 * (c & 63) + 2 * t4 + ((lane >> 4) & 1);
        const float x_res = __bfloat162float(x[red_b * DM + red_n]);
        const int cta0 = (hw * 8 + (c >> 4)) * 4, hh = (c >> 2) & 3;
        const float* q_po = &g_po[(cta0 * 4 + hh) * DH + lane * 4];
        const float* q_pml = &g_pml[(cta0 * 4 + hh) * 2];
        const float* q_in1 = &g_in1[(c * 32 + r) * 16 + 4 * t4];
        float* p_h = &g_h[((lane & 4) ? HREP / 2 : 0) * (NB * DM) + red_b * DM + red_n];
        const float* q_h = &g_h[(c % HREP) * (NB * DM) + hw * DM + lane * 4];
        const float* q_in2 = &g_in2[(c * NFCTA + r) * 16 + 4 * t4];
        __nv_bfloat16* p_out = out + red_b * DM + red_n;
        uint32_t s_ofw = s_of + (hw * 136 + lane * 4) * 2, s_hn = s_xn + hw * 1040 + lane * 8;
        uint32_t s_gu = s_red + (((hw & 1) * 2 + (lane >> 4)) * 20 + (lane & 15)) * 4;
        uint32_t s_actw = s_act + (((hw & 1) * 2 + (lane >> 4)) * 24 + (lane & 15)) * 2;
        uint32_t s_fin = s_of + lane * 4;
        pin(s_fin);
        pin(q_po); pin(q_pml); pin(q_in1); pin(p_h); pin(q_h); pin(q_in2); pin(p_out); pin(s_ofw); pin(s_hn); pin(s_gu); pin(s_actw);

#pragma unroll 1
        for (int pass = 0; pass < 2; pass++) {
            asm volatile("mov.u32 %0, %1;" : "=r"(lv) : "r"(pass));
            if (lv) {
                if (hw == 0) {
                    uint32_t it = 0;
                    while (true) {
                        const int seen = (int)(ld_rlx1(&g_count) - epoch * NCTA);
                        if (lane == 0) asm volatile("st.volatile.shared.u32 [%0], %1;" ::"r"(sbase + SM_CNT), "r"(seen) : "memory");
                        if (seen >= NCTA) break;
                        __nanosleep(seen > 0 ? 100 : 1000);
                        if (++it > SPIN_LIMIT) __trap();
                    }
                }
                asm volatile("bar.sync 10, 128;" ::: "memory");
                asm volatile("bar.sync 11, 384;" ::: "memory");
                spin_cycles(POLL_DELAY1);
            }
            {
                PollSet<4, 4 * DH, 4, 8> ps;
                poll1(ps, q_po, q_pml, tag, lv);
                const uint4 (&ov)[4] = ps.v;
                const uint2 (&ml)[4] = ps.m;
                const float M = fmaxf(fmaxf(u2f(ml[0].x), u2f(ml[1].x)), fmaxf(u2f(ml[2].x), u2f(ml[3].x)));
                const float e0 = ex2((u2f(ml[0].x) - M) * LOG2E), e1 = ex2((u2f(ml[1].x) - M) * LOG2E);
                const float e2 = ex2((u2f(ml[2].x) - M) * LOG2E), e3 = ex2((u2f(ml[3].x) - M) * LOG2E);
                const float inv = rcp_approx(fmaf(e0, u2f(ml[0].y), e1 * u2f(ml[1].y)) + fmaf(e2, u2f(ml[2].y), e3 * u2f(ml[3].y)));
                const float a0 = fmaf(e0, u2f(ov[0].x), e1 * u2f(ov[1].x)) + fmaf(e2, u2f(ov[2].x), e3 * u2f(ov[3].x));
                const float a1 = fmaf(e0, u2f(ov[0].y), e1 * u2f(ov[1].y)) + fmaf(e2, u2f(ov[2].y), e3 * u2f(ov[3].y));
                const float a2 = fmaf(e0, u2f(ov[0].z), e1 * u2f(ov[1].z)) + fmaf(e2, u2f(ov[2].z), e3 * u2f(ov[3].z));
                const float a3 = fmaf(e0, u2f(ov[0].w), e1 * u2f(ov[1].w)) + fmaf(e2, u2f(ov[2].w), e3 * u2f(ov[3].w));
                sts64(s_ofw, pack_bf16(a0 * inv, a1 * inv), pack_bf16(a2 * inv, a3 * inv), lv);
                bar_arrive_p<3, NALL>(lv);
            }
            float h_res = 0.f;
            if (hw == 3 || !lv) {
                bar_sync_p<8, NCONS + 32>(lv);
                if (lv) spin_cycles(POLL_DELAY);
                const float kk = inbox_reduce<false>(q_in1, tag, lv, lane);
                h_res = bf16r(x_res + bf16r(kk));
#pragma unroll
                for (int rp = 0; rp < HREP / 2; rp++) st_tag1(p_h + rp * (NB * DM), h_res, tag, lv);
                bar_arrive_p<7, 128>(lv);
            }
            if (hw != 3) bar_sync_p<7, 128>(lv);
            if (lv) spin_cycles(POLL_DELAY);
            if (c < NFCTA) {
                PollSet<4, 128, 0, 0> ps;
                poll1(ps, q_h, q_h, tag, lv);
                const uint4 (&u)[4] = ps.v;
                float v[16];
#pragma unroll
                for (int k = 0; k < 4; k++) {
                    v[4 * k + 0] = u2f(u[k].x & 0xffff0000u); v[4 * k + 1] = u2f(u[k].y & 0xffff0000u);
                    v[4 * k + 2] = u2f(u[k].z & 0xffff0000u); v[4 * k + 3] = u2f(u[k].w & 0xffff0000u);
                }
                warp_layernorm_store(v, __shfl_sync(0xffffffffu, v[0], 0), s_hn, lv);
                bar_arrive_p<4, NALL>(lv);
                if (hw < 2 || !lv) {
                    bar_sync_p<5, NCONS + 64>(lv);
                    float gw[8], uw[8];
#pragma unroll
                    for (int w = 0; w < 8; w++) { gw[w] = lds32(s_gu + w * 640); uw[w] = lds32(s_gu + w * 640 + 320); }
                    const float g = bf16r(((gw[0] + gw[1]) + (gw[2] + gw[3])) + ((gw[4] + gw[5]) + (gw[6] + gw[7])));
                    const float u_ = bf16r(((uw[0] + uw[1]) + (uw[2] + uw[3])) + ((uw[4] + uw[5]) + (uw[6] + uw[7])));
                    const float inner = 0.7978845608028654f * fmaf(0.044715f * g * g, g, g);
                    const float ge = bf16r(__fdividef(g, 1.f + __expf(-2.f * inner)));
                    sts16(s_actw, __bfloat16_as_ushort(__float2bfloat16_rn(ge * u_)), lv);
                    bar_arrive_p<6, NCONS + 64>(lv);
                }
            }
            if (c < NFCTA) bar_sync_p<9, NALL>(lv);
            if (lv) spin_cycles(POLL_DELAY);
            const float k2p = inbox_reduce<true>(q_in2 + hw * 28 * 16, tag, lv, lane);
            sts32(s_fin + hw * 128, k2p, lv);
            if (hw != 3) bar_arrive_p<12, 128>(lv);
            if (hw == 3 || !lv) {
                bar_sync_p<12, 128>(lv);
                const float k2 = (lds32(s_fin) + lds32(s_fin + 128)) + (lds32(s_fin + 256) + lds32(s_fin + 384));
                if (lv && !(lane & 4)) *p_out = __float2bfloat16_rn(h_res + bf16r(k2));
                if (lv && c == 0 && lane == 0) {
                    asm volatile("st.relaxed.gpu.global.u32 [%0], %1;" ::"l"(&g_epoch), "r"(epoch + 1) : "memory");
                }
            }
        }
    }
}

typedef CUresult (*EncodeFn)(CUtensorMap*, CUtensorMapDataType, cuuint32_t, void*, const cuuint64_t*, const cuuint64_t*,
                             const cuuint32_t*, const cuuint32_t*, CUtensorMapInterleave, CUtensorMapSwizzle,
                             CUtensorMapL2promotion, CUtensorMapFloatOOBfill);

CUtensorMap make_map(EncodeFn enc, const void* base, int rank, const cuuint64_t* dims, const cuuint64_t* strides,
                     const cuuint32_t* box, CUtensorMapSwizzle sw, CUtensorMapL2promotion promo) {
    CUtensorMap tm;
    cuuint32_t es[3] = {1, 1, 1};
    enc(&tm, CU_TENSOR_MAP_DATA_TYPE_BFLOAT16, rank, const_cast<void*>(base), dims, strides, box, es,
        CU_TENSOR_MAP_INTERLEAVE_NONE, sw, promo, CU_TENSOR_MAP_FLOAT_OOB_FILL_NONE);
    return tm;
}

}

extern "C" void kernel_launch(void* const* d_in, const int* in_sizes, int n_in, void* d_out, int out_size) {
    (void)in_sizes; (void)n_in; (void)out_size;
    const void* x = d_in[0];
    const void* kc = d_in[1];
    const void* vc = d_in[2];
    const void* wq = d_in[3];
    const void* wo = d_in[4];
    const void* wg = d_in[6];
    const void* wu = d_in[7];
    const void* wd = d_in[8];

    static EncodeFn enc = nullptr;
    if (!enc) {
        void* fn = nullptr;
        cudaDriverEntryPointQueryResult qr;
        cudaGetDriverEntryPoint("cuTensorMapEncodeTiled", &fn, cudaEnableDefault, &qr);
        enc = reinterpret_cast<EncodeFn>(fn);
        cudaFuncSetAttribute(fused_decode_kernel, cudaFuncAttributeMaxDynamicSharedMemorySize, SMEM_BYTES);
    }
    const auto P256 = CU_TENSOR_MAP_L2_PROMOTION_L2_256B;
    CUtensorMap tmK, tmV, tmWq, tmWo, tmWg, tmWu, tmWd;
    {
        cuuint64_t dims[3] = {64, (cuuint64_t)NB * HKV * SK, 2};
        cuuint64_t str[2] = {256, 128};
        cuuint32_t box[3] = {64, 64, 2};
        tmK = make_map(enc, kc, 3, dims, str, box, CU_TENSOR_MAP_SWIZZLE_128B, P256);
        tmV = make_map(enc, vc, 3, dims, str, box, CU_TENSOR_MAP_SWIZZLE_128B, P256);
    }
    {
        cuuint64_t dims[2] = {HQ * DH, DM};
        cuuint64_t str[1] = {HQ * DH * 2};
        cuuint32_t box[2] = {32, 256};
        tmWq = make_map(enc, wq, 2, dims, str, box, CU_TENSOR_MAP_SWIZZLE_64B, P256);
    }
    {
        cuuint64_t dims[3] = {64, HQ * DH, 8};
        cuuint64_t str[2] = {DM * 2, 128};
        cuuint32_t box[3] = {64, 64, 1};
        tmWo = make_map(enc, wo, 3, dims, str, box, CU_TENSOR_MAP_SWIZZLE_128B, P256);
    }
    {
        cuuint64_t dims[2] = {FF, DM};
        cuuint64_t str[1] = {FF * 2};
        cuuint32_t box[2] = {16, 256};
        tmWg = make_map(enc, wg, 2, dims, str, box, CU_TENSOR_MAP_SWIZZLE_32B, P256);
        tmWu = make_map(enc, wu, 2, dims, str, box, CU_TENSOR_MAP_SWIZZLE_32B, P256);
    }
    {
        cuuint64_t dims[3] = {64, FF, 8};
        cuuint64_t str[2] = {DM * 2, 128};
        cuuint32_t box[3] = {64, 16, 4};
        tmWd = make_map(enc, wd, 3, dims, str, box, CU_TENSOR_MAP_SWIZZLE_128B, P256);
    }
    fused_decode_kernel<<<NCTA, NTHREADS, SMEM_BYTES, cudaStreamPerThread>>>(
        tmK, tmV, tmWq, tmWo, tmWg, tmWu, tmWd, (const __nv_bfloat16*)x, (__nv_bfloat16*)d_out);
}
```

```cpp
#include <cuda_runtime.h>
#include <cuda_bf16.h>
#include <cuda.h>
#include <stdint.h>

namespace {

constexpr int NB = 4, DM = 512, HQ = 32, HKV = 8, SK = 8192, DH = 128, FF = 1792;
constexpr int NCTA = 128;
constexpr int NSPLIT = 4;
constexpr int TILE = 256;
constexpr int NTILE = SK / NSPLIT / TILE;
constexpr int SLOT_BYTES = 16384;
constexpr int NSLOT = 12;
constexpr int ITEM_WO = 2 + 8 * NTILE;
constexpr int ITEM_GU = ITEM_WO + 2;
constexpr int ITEM_WD = ITEM_WO + 4;
constexpr int NFCTA = FF / 16;
constexpr int HREP = 4;
constexpr int NCONS = 256;
constexpr int NHELP = 4;
constexpr int NTHREADS = NCONS + 32 + 32 * NHELP;
constexpr int NALL = NCONS + 32 * NHELP;

constexpr int WINDOW = 4;
constexpr int WINDOW_EG = 5;
constexpr int EG_COUNT = 8;
constexpr int WINDOW_T = 4;
constexpr int TRIGGER = 96;
constexpr int POLL_DELAY1 = 300;
constexpr int POLL_DELAY = 450;
constexpr uint32_t SPIN_LIMIT = 1u << 22;

constexpr int SM_MRG = NSLOT * SLOT_BYTES;
constexpr int SM_ML = SM_MRG + 8 * 4 * 136 * 4;
constexpr int SM_XN = SM_ML + 8 * 4 * 2 * 4;
constexpr int SM_QS = SM_XN + 4 * 520 * 2;
constexpr int SM_OF = SM_QS + 4 * 136 * 2;
constexpr int SM_ACT = SM_OF + 4 * 136 * 2;
constexpr int SM_BAR = SM_ACT + 4 * 24 * 2;
constexpr int SM_CNT = SM_BAR + 2 * NSLOT * 8;
constexpr int SM_WBAR = SM_CNT + 16;
constexpr int SM_TOTAL = SM_WBAR + 80;
constexpr int SMEM_BYTES = SM_TOTAL + 1024;

__device__ unsigned g_epoch;
__device__ unsigned g_count;
__device__ __align__(128) float g_q[NB * HQ * DH];
__device__ __align__(128) float g_po[NCTA * 4 * DH];
__device__ __align__(128) float g_pml[NCTA * 4 * 2];
__device__ __align__(128) float g_in1[NCTA * 32 * 16];
__device__ __align__(128) float g_h[HREP * NB * DM];
__device__ __align__(128) float g_in2[NCTA * NFCTA * 16];

__device__ __forceinline__ uint32_t smem_u32(const void* p) { return (uint32_t)__cvta_generic_to_shared(p); }
__device__ __forceinline__ void mbar_init(uint32_t bar, uint32_t cnt) {
    asm volatile("mbarrier.init.shared::cta.b64 [%0], %1;" ::"r"(bar), "r"(cnt) : "memory");
}
__device__ __forceinline__ void mbar_expect_tx(uint32_t bar, uint32_t bytes) {
    asm volatile("mbarrier.arrive.expect_tx.shared::cta.b64 _, [%0], %1;" ::"r"(bar), "r"(bytes) : "memory");
}
__device__ __forceinline__ void mbar_arrive(uint32_t bar) {
    asm volatile("mbarrier.arrive.shared::cta.b64 _, [%0];" ::"r"(bar) : "memory");
}
__device__ __forceinline__ void mbar_wait(uint32_t bar, uint32_t parity) {
    uint32_t done = 0, it = 0;
    while (true) {
        asm volatile("{\n.reg .pred p;\nmbarrier.try_wait.parity.shared::cta.b64 p, [%1], %2;\nselp.u32 %0, 1, 0, p;\n}"
                     : "=r"(done) : "r"(bar), "r"(parity) : "memory");
        if (done) break;
        if (++it > SPIN_LIMIT) __trap();
    }
}
__device__ __forceinline__ void mbar_wait_p(uint32_t bar, uint32_t parity, uint32_t lv) {
    uint32_t it = 0;
    while (true) {
        uint32_t done;
        asm volatile("{\n.reg .pred p, q;\nsetp.ne.u32 q, %3, 0;\nsetp.eq.u32 p, %3, 0;\n"
                     "@q mbarrier.try_wait.parity.shared::cta.b64 p, [%1], %2;\nselp.u32 %0, 1, 0, p;\n}"
                     : "=r"(done) : "r"(bar), "r"(parity), "r"(lv) : "memory");
        if (done) break;
        if (++it > SPIN_LIMIT) __trap();
    }
}
__device__ __forceinline__ void tma2d(uint32_t dst, const CUtensorMap* tm, int c0, int c1, uint32_t bar, uint64_t pol) {
    asm volatile("cp.async.bulk.tensor.2d.shared::cluster.global.mbarrier::complete_tx::bytes.L2::cache_hint [%0], [%1, {%3, %4}], [%2], %5;"
                 ::"r"(dst), "l"(tm), "r"(bar), "r"(c0), "r"(c1), "l"(pol) : "memory");
}
__device__ __forceinline__ void tma3d(uint32_t dst, const CUtensorMap* tm, int c0, int c1, int c2, uint32_t bar, uint64_t pol) {
    asm volatile("cp.async.bulk.tensor.3d.shared::cluster.global.mbarrier::complete_tx::bytes.L2::cache_hint [%0], [%1, {%3, %4, %5}], [%2], %6;"
                 ::"r"(dst), "l"(tm), "r"(bar), "r"(c0), "r"(c1), "r"(c2), "l"(pol) : "memory");
}
__device__ __forceinline__ void tm_prefetch(const CUtensorMap* tm) {
    asm volatile("prefetch.tensormap [%0];" ::"l"(tm) : "memory");
}
__device__ __forceinline__ void ldsm4(uint32_t (&r)[4], uint32_t addr) {
    asm volatile("ldmatrix.sync.aligned.m8n8.x4.shared.b16 {%0,%1,%2,%3}, [%4];"
                 : "=r"(r[0]), "=r"(r[1]), "=r"(r[2]), "=r"(r[3]) : "r"(addr) : "memory");
}
__device__ __forceinline__ void ldsm4t(uint32_t (&r)[4], uint32_t addr) {
    asm volatile("ldmatrix.sync.aligned.m8n8.x4.trans.shared.b16 {%0,%1,%2,%3}, [%4];"
                 : "=r"(r[0]), "=r"(r[1]), "=r"(r[2]), "=r"(r[3]) : "r"(addr) : "memory");
}
__device__ __forceinline__ void mma16816(float (&c)[4], const uint32_t (&a)[4], uint32_t b0, uint32_t b1) {
    asm volatile("mma.sync.aligned.m16n8k16.row.col.f32.bf16.bf16.f32 {%0,%1,%2,%3}, {%4,%5,%6,%7}, {%8,%9}, {%0,%1,%2,%3};"
                 : "+f"(c[0]), "+f"(c[1]), "+f"(c[2]), "+f"(c[3])
                 : "r"(a[0]), "r"(a[1]), "r"(a[2]), "r"(a[3]), "r"(b0), "r"(b1));
}
__device__ __forceinline__ uint32_t movm_t(uint32_t a) {
    uint32_t d;
    asm volatile("movmatrix.sync.aligned.m8n8.trans.b16 %0, %1;" : "=r"(d) : "r"(a));
    return d;
}
__device__ __forceinline__ uint32_t pack_bf16(float lo, float hi) {
    uint32_t d;
    asm("cvt.rn.bf16x2.f32 %0, %1, %2;" : "=r"(d) : "f"(hi), "f"(lo));
    return d;
}
__device__ __forceinline__ float bf16r(float x) { return __bfloat162float(__float2bfloat16_rn(x)); }
__device__ __forceinline__ float bf_lo(uint32_t w) { return __uint_as_float(w << 16); }
__device__ __forceinline__ float bf_hi(uint32_t w) { return __uint_as_float(w & 0xffff0000u); }
__device__ __forceinline__ float ex2(float x) {
    float y;
    asm("ex2.approx.ftz.f32 %0, %1;" : "=f"(y) : "f"(x));
    return y;
}
__device__ __forceinline__ void cons_sync() { asm volatile("bar.sync 1, 256;" ::: "memory"); }
template <int ID, int CNT> __device__ __forceinline__ void bar_sync_p(uint32_t lv) {
    asm volatile("{\n.reg .pred q;\nsetp.ne.u32 q, %0, 0;\n@q bar.sync %1, %2;\n}" ::"r"(lv), "n"(ID), "n"(CNT) : "memory");
}
template <int ID, int CNT> __device__ __forceinline__ void bar_arrive_p(uint32_t lv) {
    asm volatile("{\n.reg .pred q;\nsetp.ne.u32 q, %0, 0;\n@q bar.arrive %1, %2;\n}" ::"r"(lv), "n"(ID), "n"(CNT) : "memory");
}
__device__ __forceinline__ void spin_cycles(uint32_t n) {
    const uint32_t t0 = (uint32_t)clock();
    while ((uint32_t)clock() - t0 < n) {}
}
__device__ __forceinline__ void sts32(uint32_t a, float v, uint32_t p) {
    asm volatile("{\n.reg .pred q;\nsetp.ne.u32 q, %2, 0;\n@q st.shared.f32 [%0], %1;\n}" ::"r"(a), "f"(v), "r"(p) : "memory");
}
__device__ __forceinline__ void sts16(uint32_t a, uint16_t v, uint32_t p) {
    asm volatile("{\n.reg .pred q;\nsetp.ne.u32 q, %2, 0;\n@q st.shared.u16 [%0], %1;\n}" ::"r"(a), "h"(v), "r"(p) : "memory");
}
__device__ __forceinline__ void sts64(uint32_t a, uint32_t x, uint32_t y, uint32_t p) {
    asm volatile("{\n.reg .pred q;\nsetp.ne.u32 q, %3, 0;\n@q st.shared.v2.u32 [%0], {%1, %2};\n}" ::"r"(a), "r"(x), "r"(y), "r"(p) : "memory");
}
__device__ __forceinline__ float lds32(uint32_t a) {
    float v; asm volatile("ld.shared.f32 %0, [%1];" : "=f"(v) : "r"(a) : "memory"); return v;
}
__device__ __forceinline__ float2 lds64(uint32_t a) {
    float2 v; asm volatile("ld.shared.v2.f32 {%0, %1}, [%2];" : "=f"(v.x), "=f"(v.y) : "r"(a) : "memory"); return v;
}

__device__ __forceinline__ float u2f(uint32_t u) { return __uint_as_float(u); }
__device__ __forceinline__ float tagf(float v, uint32_t tag) { return __uint_as_float((__float_as_uint(v) & ~1u) | tag); }
__device__ __forceinline__ void st_tag1(float* ptr, float v, uint32_t tag, uint32_t p) {
    asm volatile("{\n.reg .pred q;\nsetp.ne.u32 q, %2, 0;\n@q st.relaxed.gpu.global.f32 [%0], %1;\n}"
                 ::"l"(ptr), "f"(tagf(v, tag)), "r"(p) : "memory");
}
__device__ __forceinline__ void st_tag2(float* ptr, float a, float b, uint32_t tag, uint32_t p) {
    asm volatile("{\n.reg .pred q;\nsetp.ne.u32 q, %3, 0;\n@q st.relaxed.gpu.global.v2.f32 [%0], {%1, %2};\n}"
                 ::"l"(ptr), "f"(tagf(a, tag)), "f"(tagf(b, tag)), "r"(p) : "memory");
}
__device__ __forceinline__ void ld_rlx4(uint4& v, const float* ptr, uint32_t p) {
    asm volatile("{\n.reg .pred q;\nsetp.ne.u32 q, %5, 0;\n@q ld.relaxed.gpu.global.v4.u32 {%0,%1,%2,%3}, [%4];\n}"
                 : "+r"(v.x), "+r"(v.y), "+r"(v.z), "+r"(v.w) : "l"(ptr), "r"(p) : "memory");
}
__device__ __forceinline__ void ld_rlx2(uint2& v, const float* ptr, uint32_t p) {
    asm volatile("{\n.reg .pred q;\nsetp.ne.u32 q, %3, 0;\n@q ld.relaxed.gpu.global.v2.u32 {%0,%1}, [%2];\n}"
                 : "+r"(v.x), "+r"(v.y) : "l"(ptr), "r"(p) : "memory");
}
__device__ __forceinline__ uint32_t ld_rlx1(const unsigned* p) {
    uint32_t v;
    asm volatile("ld.relaxed.gpu.global.u32 %0, [%1];" : "=r"(v) : "l"(p) : "memory");
    return v;
}
__device__ __forceinline__ uint32_t bad4(const uint4& v, uint32_t tag) {
    uint32_t u, w, r;
    asm("lop3.b32 %0, %1, %2, %3, 0x7E;" : "=r"(u) : "r"(v.x), "r"(v.y), "r"(tag));
    asm("lop3.b32 %0, %1, %2, %3, 0x7E;" : "=r"(w) : "r"(v.z), "r"(v.w), "r"(tag));
    asm("lop3.b32 %0, %1, %2, 1, 0xA8;" : "=r"(r) : "r"(u), "r"(w));
    return r;
}
__device__ __forceinline__ uint32_t bad2(const uint2& v, uint32_t tag) {
    uint32_t u;
    asm("lop3.b32 %0, %1, %2, %3, 0x7E;" : "=r"(u) : "r"(v.x), "r"(v.y), "r"(tag));
    return u & 1u;
}
template <typename T> __device__ __forceinline__ void pin(T*& p) { asm volatile("" : "+l"(p)); }
__device__ __forceinline__ void pin(uint32_t& v) { asm volatile("" : "+r"(v)); }
__device__ __forceinline__ float sqrt_approx(float x) { float y; asm("sqrt.approx.ftz.f32 %0, %1;" : "=f"(y) : "f"(x)); return y; }
__device__ __forceinline__ float rcp_approx(float x) { float y; asm("rcp.approx.ftz.f32 %0, %1;" : "=f"(y) : "f"(x)); return y; }
template <int NK, int KS, int NM, int MS>
struct PollSet {
    uint4 v[NK]; uint2 m[NM > 0 ? NM : 1]; uint32_t bad[NK], badm[NM > 0 ? NM : 1];
    __device__ __forceinline__ void init(uint32_t tag, uint32_t lv) {
#pragma unroll
        for (int k = 0; k < NK; k++) { v[k] = make_uint4(tag, tag, tag, tag); bad[k] = lv; }
#pragma unroll
        for (int k = 0; k < NM; k++) { m[k] = make_uint2(tag, tag); badm[k] = lv; }
    }
    __device__ __forceinline__ void issue(const float* src, const float* src2) {
#pragma unroll
        for (int k = 0; k < NK; k++) ld_rlx4(v[k], src + k * KS, bad[k]);
#pragma unroll
        for (int k = 0; k < NM; k++) ld_rlx2(m[k], src2 + k * MS, badm[k]);
    }
    __device__ __forceinline__ bool complete(uint32_t tag) {
        uint32_t any = 0;
#pragma unroll
        for (int k = 0; k < NK; k++) { bad[k] = bad4(v[k], tag); any |= bad[k]; }
#pragma unroll
        for (int k = 0; k < NM; k++) { badm[k] = bad2(m[k], tag); any |= badm[k]; }
        return !__any_sync(0xffffffffu, any);
    }
};
constexpr float LOG2E = 1.4426950408889634f;

__device__ __forceinline__ void warp_layernorm_store(const float (&v)[16], float c, uint32_t dst, uint32_t p) {
    float s1[4], s2[4];
#pragma unroll
    for (int k = 0; k < 4; k++) {
        const float d0 = v[4 * k] - c, d1 = v[4 * k + 1] - c, d2 = v[4 * k + 2] - c, d3 = v[4 * k + 3] - c;
        s1[k] = (d0 + d1) + (d2 + d3);
        s2[k] = fmaf(d0, d0, d1 * d1) + fmaf(d2, d2, d3 * d3);
    }
    float t1 = (s1[0] + s1[1]) + (s1[2] + s1[3]), t2 = (s2[0] + s2[1]) + (s2[2] + s2[3]);
#pragma unroll
    for (int o = 16; o > 0; o >>= 1) {
        t1 += __shfl_xor_sync(0xffffffffu, t1, o);
        t2 += __shfl_xor_sync(0xffffffffu, t2, o);
    }
    const float md = t1 * (1.f / 512.f);
    const float mean = bf16r(c + md);
    const float var = bf16r(fmaxf(fmaf(-md, md, t2 * (1.f / 512.f)), 0.f));
    const float inv = rcp_approx(bf16r(sqrt_approx(bf16r(var + 1e-5f))));
#pragma unroll
    for (int k = 0; k < 4; k++) {
        const uint32_t t01 = pack_bf16(v[4 * k + 0] - mean, v[4 * k + 1] - mean);
        const uint32_t t23 = pack_bf16(v[4 * k + 2] - mean, v[4 * k + 3] - mean);
        sts64(dst + k * 256, pack_bf16(bf_lo(t01) * inv, bf_hi(t01) * inv), pack_bf16(bf_lo(t23) * inv, bf_hi(t23) * inv), p);
    }
}

template <class PS>
__device__ __forceinline__ void poll1(PS& ps, const float* src, const float* src2, uint32_t tag, uint32_t lv) {
    ps.init(tag, lv);
    uint32_t it = 0;
    while (true) {
        ps.issue(src, src2);
        if (ps.complete(tag)) break;
        if (++it > SPIN_LIMIT) __trap();
    }
}
template <bool PART>
__device__ __forceinline__ float inbox_reduce(const float* src, uint32_t tag, uint32_t lv, int lane) {
    PollSet<4, 128, 0, 0> ps;
    ps.init(tag, lv);
    const bool last = !PART || (lane >> 2) < 4;
    if (!last) ps.bad[3] = 0;
    uint32_t it = 0;
    while (true) {
        ps.issue(src, src);
        if (ps.complete(tag)) break;
        if (++it > SPIN_LIMIT) __trap();
    }
    const float m3 = last ? 1.f : 0.f;
    const float a = (u2f(ps.v[0].x) + u2f(ps.v[1].x)) + fmaf(m3, u2f(ps.v[3].x), u2f(ps.v[2].x));
    const float b = (u2f(ps.v[0].y) + u2f(ps.v[1].y)) + fmaf(m3, u2f(ps.v[3].y), u2f(ps.v[2].y));
    const float c = (u2f(ps.v[0].z) + u2f(ps.v[1].z)) + fmaf(m3, u2f(ps.v[3].z), u2f(ps.v[2].z));
    const float d = (u2f(ps.v[0].w) + u2f(ps.v[1].w)) + fmaf(m3, u2f(ps.v[3].w), u2f(ps.v[2].w));
    const bool hi = lane & 16, h2 = lane & 8;
    float k0 = hi ? c : a, k1 = hi ? d : b;
    k0 += __shfl_xor_sync(0xffffffffu, hi ? a : c, 16);
    k1 += __shfl_xor_sync(0xffffffffu, hi ? b : d, 16);
    float kk = h2 ? k1 : k0;
    kk += __shfl_xor_sync(0xffffffffu, h2 ? k0 : k1, 8);
    kk += __shfl_xor_sync(0xffffffffu, kk, 4);
    return kk;
}


__global__ void __launch_bounds__(NTHREADS, 1)
fused_decode_kernel(const __grid_constant__ CUtensorMap tmK, const __grid_constant__ CUtensorMap tmV,
                    const __grid_constant__ CUtensorMap tmWq, const __grid_constant__ CUtensorMap tmWo,
                    const __grid_constant__ CUtensorMap tmWg, const __grid_constant__ CUtensorMap tmWu,
                    const __grid_constant__ CUtensorMap tmWd,
                    const __nv_bfloat16* __restrict__ x, __nv_bfloat16* __restrict__ out) {
    extern __shared__ uint8_t smem_raw[];
    const uint32_t sbase = (smem_u32(smem_raw) + 1023u) & ~1023u;
    const uint32_t bar_full = sbase + SM_BAR, bar_empty = bar_full + NSLOT * 8;
    const int tid = threadIdx.x, lane = tid & 31;
    const int c = blockIdx.x;
    const int row0 = (c >> 2) * SK + (c & 3) * (SK / NSPLIT);
    uint64_t pol_stream = 0;
    if (tid == NCONS) {
        tm_prefetch(&tmWq); tm_prefetch(&tmK); tm_prefetch(&tmV);
        for (int i = 0; i < 4; i++) mbar_init(bar_full + 8 * i, 1);
        asm volatile("fence.proxy.async.shared::cta;" ::: "memory");
        asm volatile("createpolicy.fractional.L2::evict_first.b64 %0, 1.0;" : "=l"(pol_stream));
        mbar_expect_tx(bar_full, SLOT_BYTES);
        tma2d(sbase, &tmWq, 32 * c, 0, bar_full, pol_stream);
        mbar_expect_tx(bar_full + 8, SLOT_BYTES);
        tma2d(sbase + SLOT_BYTES, &tmWq, 32 * c, 256, bar_full + 8, pol_stream);
        mbar_expect_tx(bar_full + 16, SLOT_BYTES);
        tma3d(sbase + 2 * SLOT_BYTES, &tmK, 0, row0, 0, bar_full + 16, pol_stream);
        mbar_expect_tx(bar_full + 24, SLOT_BYTES);
        tma3d(sbase + 3 * SLOT_BYTES, &tmK, 0, row0 + 64, 0, bar_full + 24, pol_stream);
        for (int i = 4; i < NSLOT; i++) mbar_init(bar_full + 8 * i, 1);
        for (int i = 0; i < NSLOT; i++) mbar_init(bar_empty + 8 * i, 4);
        for (int i = 0; i < 10; i++) mbar_init(sbase + SM_WBAR + 8 * i, 1);
        asm volatile("fence.proxy.async.shared::cta;" ::: "memory");
        asm volatile("st.volatile.shared.u32 [%0], %1;" ::"r"(sbase + SM_CNT), "r"(0) : "memory");
    }
    __syncthreads();

    if ((tid >> 5) == 8) {
        if (lane == 0) {
            auto acquire = [&](int i, int window) {
                if (i >= NSLOT) mbar_wait(bar_empty + 8 * (i % NSLOT), ((i / NSLOT) - 1) & 1);
                if (i >= window) { const int j = i - window; mbar_wait(bar_full + 8 * (j % NSLOT), (j / NSLOT) & 1); }
            };
            auto seen_count = [&]() {
                uint32_t seen;
                asm volatile("ld.volatile.shared.u32 %0, [%1];" : "=r"(seen) : "r"(sbase + SM_CNT) : "memory");
                return (int)seen;
            };
#pragma unroll 1
            for (int i = 4; i < ITEM_WO; i++) {
                const int slot = i % NSLOT;
                acquire(i, (i >= ITEM_WO - 24 && seen_count() >= EG_COUNT) ? WINDOW_EG : WINDOW);
                mbar_expect_tx(bar_full + 8 * slot, SLOT_BYTES);
                tma3d(sbase + slot * SLOT_BYTES, (((i - 2) >> 2) & 1) ? &tmV : &tmK, 0, row0 + ((i - 2) >> 3) * TILE + ((i - 2) & 3) * 64, 0,
                      bar_full + 8 * slot, pol_stream);
            }
            asm volatile("red.relaxed.gpu.global.add.u32 [%0], 1;" ::"l"(&g_count) : "memory");
            {
                uint32_t it = 0;
                while (seen_count() < TRIGGER) {
                    __nanosleep(20);
                    if (++it > SPIN_LIMIT) __trap();
                }
            }
            const int npiece = (c < NFCTA) ? 10 : 4;
#pragma unroll 1
            for (int j = 0; j < npiece; j++) {
                const int item = j < 4 ? ITEM_WO + (j >> 1) : (j < 8 ? ITEM_GU + ((j - 4) >> 1) : ITEM_WD + (j - 8));
                const int slot = item % NSLOT;
                mbar_wait(bar_empty + 8 * slot, ((item / NSLOT) - 1) & 1);
                if (j >= WINDOW_T) mbar_wait(sbase + SM_WBAR + 8 * (j - WINDOW_T), 0);
                else if (j < 2) { const int jj = ITEM_WO - 2 + j; mbar_wait(bar_full + 8 * (jj % NSLOT), (jj / NSLOT) & 1); }
                const uint32_t fb = sbase + SM_WBAR + 8 * j, dst = sbase + slot * SLOT_BYTES + ((j < 8) ? (j & 1) * 8192 : 0);
                mbar_expect_tx(fb, 8192);
                if (j < 4) tma3d(dst, &tmWo, 0, 128 * (c >> 2) + 64 * (j & 1), 2 * (c & 3) + (j >> 1), fb, pol_stream);
                else if (j < 8) tma2d(dst, (j & 1) ? &tmWu : &tmWg, 16 * c, 256 * ((j - 4) >> 1), fb, pol_stream);
                else tma3d(dst, &tmWd, 0, 16 * c, 4 * (j - 8), fb, pol_stream);
            }
        }
        return;
    }

    uint32_t lv;
    asm volatile("mov.u32 %0, %1;" : "=r"(lv) : "r"((tid < NCONS) ? 1u : 0u));
    const int warp = lv ? (tid >> 5) : 0;
    const int vtid = warp * 32 + lane;
    const int r = lane >> 2, t4 = lane & 3;
    const int wg = warp >> 2, wl = warp & 3;
    const uint32_t s_red = sbase + SM_MRG, s_ml = sbase + SM_ML, s_xn = sbase + SM_XN;
    const uint32_t s_qs = sbase + SM_QS, s_of = sbase + SM_OF, s_act = sbase + SM_ACT;
    const int brow = lane & 3, bch = lane >> 3;

    uint2 xw[4];
#pragma unroll
    for (int k = 0; k < 4; k++) {
        xw[k] = make_uint2(0u, 0u);
        asm volatile("{\n.reg .pred q;\nsetp.ne.u32 q, %3, 0;\n@q ld.global.nc.v2.u32 {%0, %1}, [%2];\n}"
                     : "+r"(xw[k].x), "+r"(xw[k].y) : "l"(x + (warp & 3) * DM + k * 128 + lane * 4), "r"((uint32_t)(lv && warp < NB)));
    }
    const unsigned epoch = ld_rlx1(&g_epoch);
    uint32_t tag = 0;

    float* p_po = &g_po[(c * 4 + (vtid >> 6)) * DH + (vtid & 63) * 2];
    float* p_pml = &g_pml[(c * 4 + (vtid >> 6)) * 2];
    float* p_in1 = &g_in1[((t4 * 64 + 16 * (c & 3) + 2 * warp) * 32 + (c >> 2)) * 16 + 2 * r];
    float* p_in2 = &g_in2[((t4 * 64 + 8 * warp) * NFCTA + (c < NFCTA ? c : 0)) * 16 + 2 * r];
    pin(p_po); pin(p_pml); pin(p_in1); pin(p_in2);

    float o[8][4];
#pragma unroll
    for (int j = 0; j < 8; j++) { o[j][0] = o[j][1] = o[j][2] = o[j][3] = 0.f; }
    float mfin0 = 0.f, mfin1 = 0.f;

    if (lv) {
        if (warp < NB) {
            float v[16];
#pragma unroll
            for (int k = 0; k < 4; k++) {
                const uint2 w = xw[k];
                v[4 * k + 0] = bf_lo(w.x); v[4 * k + 1] = bf_hi(w.x); v[4 * k + 2] = bf_lo(w.y); v[4 * k + 3] = bf_hi(w.y);
            }
            warp_layernorm_store(v, __shfl_sync(0xffffffffu, v[0], 0), s_xn + warp * 1040 + lane * 8, 1u);
        }
        cons_sync();
        asm volatile("lop3.b32 %0, %1, 1, 1, 0x6A;" : "=r"(tag) : "r"(epoch));

        mbar_wait(bar_full + 8 * wg, 0);
        {
            float acc[2][4] = {};
#pragma unroll
            for (int kp = 0; kp < 2; kp++) {
                uint32_t b[4];
                ldsm4(b, s_xn + brow * 1040 + (warp * 64 + kp * 32 + bch * 8) * 2);
#pragma unroll
                for (int k2 = 0; k2 < 2; k2++) {
                    const int krow = warp * 64 + kp * 32 + k2 * 16 + (lane & 7) + ((lane >> 4) << 3);
#pragma unroll
                    for (int mt = 0; mt < 2; mt++) {
                        const int chunk = mt * 2 + ((lane >> 3) & 1);
                        uint32_t a[4];
                        ldsm4t(a, sbase + krow * 64 + ((chunk ^ ((krow >> 1) & 3)) << 4));
                        mma16816(acc[mt], a, b[2 * k2], b[2 * k2 + 1]);
                    }
                }
            }
            __syncwarp();
            if (lane == 0) mbar_arrive(bar_empty + 8 * wg);
            const uint32_t pq = t4 < 2;
#pragma unroll
            for (int mt = 0; mt < 2; mt++) {
                const uint32_t dst = s_red + (warp * 144 + (2 * t4) * 36 + mt * 16 + r) * 4;
                sts32(dst, acc[mt][0], pq); sts32(dst + 144, acc[mt][1], pq);
                sts32(dst + 32, acc[mt][2], pq); sts32(dst + 144 + 32, acc[mt][3], pq);
            }
            cons_sync();
            if (tid < 128) {
                float s = 0.f;
#pragma unroll
                for (int w = 0; w < 8; w++) s += lds32(s_red + (w * 144 + warp * 36 + lane) * 4);
                st_tag1(&g_q[warp * (HQ * DH) + 32 * c + lane], bf16r(s), tag, 1u);
                const int g = c >> 2;
                const float* src = &g_q[(g >> 3) * (HQ * DH) + (g & 7) * 512 + tid * 4];
                uint4 v;
                uint32_t it = 0;
                while (true) {
                    ld_rlx4(v, src, 1u);
                    if (!(bad4(v, tag) & 1)) break;
                    if (++it > SPIN_LIMIT) __trap();
                }
                sts64(s_qs + (warp * 136 + lane * 4) * 2, (v.x >> 16) | (v.y & 0xffff0000u), (v.z >> 16) | (v.w & 0xffff0000u), 1u);
            }
            cons_sync();
        }

        uint32_t qf[8][2];
#pragma unroll
        for (int j = 0; j < 8; j += 2) {
            uint32_t b[4];
            ldsm4(b, s_qs + brow * 272 + (j * 16 + bch * 8) * 2);
            qf[j][0] = b[0]; qf[j][1] = b[1]; qf[j + 1][0] = b[2]; qf[j + 1][1] = b[3];
        }
        const int krow = wl * 16 + (lane & 7) + (((lane >> 3) & 1) << 3);
        const int kch = lane >> 4;
        const int vrow = wl * 16 + (lane & 7) + ((lane >> 4) << 3);
        const int vch = (lane >> 3) & 1;
        const float scale = 0.08838834764831845f;
        float m0 = -INFINITY, m1 = -INFINITY, l0 = 0.f, l1 = 0.f;

#pragma unroll 1
        for (int t = 0; t < NTILE; t++) {
            float sc[2][4];
#pragma unroll
            for (int a = 0; a < 2; a++) {
                const int ik = 2 + 8 * t + 2 * a + wg;
                const int sk = ik % NSLOT;
                mbar_wait(bar_full + 8 * sk, (ik / NSLOT) & 1);
                float sa[4] = {0.f, 0.f, 0.f, 0.f}, sb[4] = {0.f, 0.f, 0.f, 0.f};
                const uint32_t kb = sbase + sk * SLOT_BYTES + krow * 128;
#pragma unroll
                for (int j = 0; j < 8; j += 2) {
                    uint32_t a0[4], a1[4];
                    ldsm4(a0, kb + (j >> 2) * 8192 + (((((j & 3) << 1) + kch) ^ (krow & 7)) << 4));
                    ldsm4(a1, kb + ((j + 1) >> 2) * 8192 + ((((((j + 1) & 3) << 1) + kch) ^ (krow & 7)) << 4));
                    mma16816(sa, a0, qf[j][0], qf[j][1]);
                    mma16816(sb, a1, qf[j + 1][0], qf[j + 1][1]);
                }
                __syncwarp();
                if (lane == 0) mbar_arrive(bar_empty + 8 * sk);
#pragma unroll
                for (int e = 0; e < 4; e++) sc[a][e] = bf16r(bf16r(sa[e] + sb[e]) * scale);
            }
            float x0 = fmaxf(fmaxf(fmaxf(sc[0][0], sc[0][2]), fmaxf(sc[1][0], sc[1][2])), m0);
            float x1 = fmaxf(fmaxf(fmaxf(sc[0][1], sc[0][3]), fmaxf(sc[1][1], sc[1][3])), m1);
#pragma unroll
            for (int off = 4; off < 32; off <<= 1) {
                x0 = fmaxf(x0, __shfl_xor_sync(0xffffffffu, x0, off));
                x1 = fmaxf(x1, __shfl_xor_sync(0xffffffffu, x1, off));
            }
            if (t == NTILE - 1) {
                sts64(s_ml + (warp * 4 + t4 * 2) * 4, __float_as_uint(x0), __float_as_uint(x1), r == 0 && t4 < 2);
                cons_sync();
#pragma unroll
                for (int w = 0; w < 8; w++) {
                    const float2 mw = lds64(s_ml + (w * 4 + (t4 & 1) * 2) * 4);
                    x0 = fmaxf(x0, mw.x); x1 = fmaxf(x1, mw.y);
                }
            }
            if (__any_sync(0xffffffffu, (x0 > m0) || (x1 > m1))) {
                const float a0 = ex2((m0 - x0) * LOG2E), a1 = ex2((m1 - x1) * LOG2E);
                m0 = x0; m1 = x1;
                l0 *= a0; l1 *= a1;
#pragma unroll
                for (int j = 0; j < 8; j++) { o[j][0] *= a0; o[j][1] *= a1; o[j][2] *= a0; o[j][3] *= a1; }
            }
            uint32_t pb[2][2];
#pragma unroll
            for (int a = 0; a < 2; a++) {
                const float p0 = ex2((sc[a][0] - m0) * LOG2E), p1 = ex2((sc[a][1] - m1) * LOG2E);
                const float p2 = ex2((sc[a][2] - m0) * LOG2E), p3 = ex2((sc[a][3] - m1) * LOG2E);
                l0 += p0 + p2; l1 += p1 + p3;
                pb[a][0] = movm_t(pack_bf16(p0, p1));
                pb[a][1] = movm_t(pack_bf16(p2, p3));
            }
            if (t == NTILE - 1) {
#pragma unroll
                for (int off = 4; off < 32; off <<= 1) {
                    l0 += __shfl_xor_sync(0xffffffffu, l0, off);
                    l1 += __shfl_xor_sync(0xffffffffu, l1, off);
                }
                sts64(s_ml + 128 + (warp * 4 + t4 * 2) * 4, __float_as_uint(l0), __float_as_uint(l1), r == 0 && t4 < 2);
            }
#pragma unroll
            for (int a = 0; a < 2; a++) {
                const int iv = 2 + 8 * t + 4 + 2 * a + wg;
                const int sv = iv % NSLOT;
                mbar_wait(bar_full + 8 * sv, (iv / NSLOT) & 1);
                const uint32_t vb = sbase + sv * SLOT_BYTES + vrow * 128;
#pragma unroll
                for (int j = 0; j < 8; j++) {
                    uint32_t av[4];
                    ldsm4t(av, vb + (j >> 2) * 8192 + (((((j & 3) << 1) + vch) ^ (vrow & 7)) << 4));
                    mma16816(o[j], av, pb[a][0], pb[a][1]);
                }
                __syncwarp();
                if (lane == 0) mbar_arrive(bar_empty + 8 * sv);
            }
        }
        mfin0 = m0; mfin1 = m1;
    } else {
        tag = (epoch & 1u) ^ 1u;
        __nanosleep(6000);
        const int wt = tid - (NCONS + 32);
        const float z = __uint_as_float(tag ^ 1u);
        auto st4 = [&](float* p) {
            asm volatile("st.relaxed.gpu.global.v4.f32 [%0], {%1, %1, %1, %1};" ::"l"(p), "f"(z) : "memory");
        };
        st4(&g_po[c * 512 + wt * 4]);
        st4(&g_in1[((((wt >> 2) >> 4) * 64 + 16 * (c & 3) + ((wt >> 2) & 15)) * 32 + (c >> 2)) * 16 + (wt & 3) * 4]);
        if (c < NFCTA)
            for (int i = wt; i < 512; i += 128) st4(&g_in2[((i >> 2) * NFCTA + c) * 16 + (i & 3) * 4]);
        if (wt < 16) st4(&g_h[(wt >> 2) * (NB * DM) + (2 * (c >> 6) + ((wt >> 1) & 1)) * DM + 8 * (c & 63) + (wt & 1) * 4]);
        else if (wt < 18) st4(&g_pml[c * 8 + (wt - 16) * 4]);
        asm volatile("bar.arrive 2, %0;" ::"n"(NALL) : "memory");
    }

    const uint32_t pw = lv && (t4 < 2);
    {
        const uint32_t dst = s_red + (warp * 544 + (2 * t4) * 136 + r) * 4;
#pragma unroll
        for (int j = 0; j < 8; j++) {
            sts32(dst + j * 64, o[j][0], pw);
            sts32(dst + 544 + j * 64, o[j][1], pw);
            sts32(dst + j * 64 + 32, o[j][2], pw);
            sts32(dst + 544 + j * 64 + 32, o[j][3], pw);
        }
        const int h = vtid >> 6;
        const uint32_t src = s_red + (h * 136 + (vtid & 63) * 2) * 4;
        const float Mh = __shfl_sync(0xffffffffu, (h & 1) ? mfin1 : mfin0, h >> 1);
        bar_sync_p<2, NALL>(lv);
        float2 ov[8]; float lw[8];
#pragma unroll
        for (int w = 0; w < 8; w++) { ov[w] = lds64(src + w * 2176); lw[w] = lds32(s_ml + 128 + (w * 4 + h) * 4); }
        const float a0 = ((ov[0].x + ov[1].x) + (ov[2].x + ov[3].x)) + ((ov[4].x + ov[5].x) + (ov[6].x + ov[7].x));
        const float a1 = ((ov[0].y + ov[1].y) + (ov[2].y + ov[3].y)) + ((ov[4].y + ov[5].y) + (ov[6].y + ov[7].y));
        const float L = ((lw[0] + lw[1]) + (lw[2] + lw[3])) + ((lw[4] + lw[5]) + (lw[6] + lw[7]));
        st_tag2(p_po, a0, a1, tag, lv);
        st_tag2(p_pml, Mh, L, tag, lv && (vtid & 63) == 0);
        bar_arrive_p<11, NALL>(lv);
    }
    {
        const int slot = (ITEM_WO + wg) % NSLOT;
        mbar_wait_p(sbase + SM_WBAR + 8 * (2 * wg), 0, lv);
        mbar_wait_p(sbase + SM_WBAR + 8 * (2 * wg + 1), 0, lv);
        const int krow = (lane & 7) + ((lane >> 4) << 3);
        const uint32_t wb = sbase + slot * SLOT_BYTES + krow * 128 + ((((wl << 1) + ((lane >> 3) & 1)) ^ (krow & 7)) << 4);
        uint32_t a[8][4];
#pragma unroll
        for (int ks = 0; ks < 8; ks++) ldsm4t(a[ks], wb + ks * 2048);
        uint32_t sb = s_of + brow * 272 + bch * 16;
        pin(sb);
        bar_sync_p<3, NALL>(lv);
        uint32_t b[4][4];
#pragma unroll
        for (int kp = 0; kp < 4; kp++) ldsm4(b[kp], sb + kp * 64);
        float acc[4][4] = {};
#pragma unroll
        for (int kp = 0; kp < 4; kp++) {
            mma16816(acc[kp], a[2 * kp], b[kp][0], b[kp][1]);
            mma16816(acc[kp], a[2 * kp + 1], b[kp][2], b[kp][3]);
        }
        st_tag2(p_in1, (acc[0][0] + acc[1][0]) + (acc[2][0] + acc[3][0]), (acc[0][1] + acc[1][1]) + (acc[2][1] + acc[3][1]), tag, pw);
        st_tag2(p_in1 + 32 * 16, (acc[0][2] + acc[1][2]) + (acc[2][2] + acc[3][2]), (acc[0][3] + acc[1][3]) + (acc[2][3] + acc[3][3]), tag, pw);
        bar_arrive_p<8, NCONS + 32>(lv);
    }
    if (c < NFCTA) {
        uint32_t ag[4][4], au[4][4], ad[4][4];
        {
            const int slot = (ITEM_GU + wg) % NSLOT;
            mbar_wait_p(sbase + SM_WBAR + 8 * (4 + 2 * wg), 0, lv);
            mbar_wait_p(sbase + SM_WBAR + 8 * (5 + 2 * wg), 0, lv);
            const int krow = wl * 64 + (lane & 7) + ((lane >> 4) << 3);
            const uint32_t gb = sbase + slot * SLOT_BYTES + krow * 32 + ((((lane >> 3) & 1) ^ ((krow >> 2) & 1)) << 4);
#pragma unroll
            for (int ks = 0; ks < 4; ks++) { ldsm4t(ag[ks], gb + ks * 512); ldsm4t(au[ks], gb + 8192 + ks * 512); }
        }
        uint32_t sb = s_xn + brow * 1040 + (warp * 64 + bch * 8) * 2;
        uint32_t sd = s_red + (warp * 160 + (2 * t4) * 20 + r) * 4;
        uint32_t sa = s_act + brow * 48 + (bch & 1) * 16;
        pin(sb); pin(sd); pin(sa);
        bar_sync_p<4, NALL>(lv);
        {
            uint32_t b0[4], b1[4];
            ldsm4(b0, sb); ldsm4(b1, sb + 64);
            float g0[4] = {}, g1[4] = {}, u0[4] = {}, u1[4] = {};
            mma16816(g0, ag[0], b0[0], b0[1]); mma16816(u0, au[0], b0[0], b0[1]);
            mma16816(g1, ag[2], b1[0], b1[1]); mma16816(u1, au[2], b1[0], b1[1]);
            mma16816(g0, ag[1], b0[2], b0[3]); mma16816(u0, au[1], b0[2], b0[3]);
            mma16816(g1, ag[3], b1[2], b1[3]); mma16816(u1, au[3], b1[2], b1[3]);
            sts32(sd, g0[0] + g1[0], pw);        sts32(sd + 80, g0[1] + g1[1], pw);
            sts32(sd + 32, g0[2] + g1[2], pw);   sts32(sd + 80 + 32, g0[3] + g1[3], pw);
            sts32(sd + 320, u0[0] + u1[0], pw);      sts32(sd + 320 + 80, u0[1] + u1[1], pw);
            sts32(sd + 320 + 32, u0[2] + u1[2], pw); sts32(sd + 320 + 80 + 32, u0[3] + u1[3], pw);
            bar_arrive_p<5, NCONS + 64>(lv);
        }
        {
            const int slot = (ITEM_WD + wg) % NSLOT;
            mbar_wait_p(sbase + SM_WBAR + 8 * (8 + wg), 0, lv);
            const int krow = (lane & 7) + ((lane >> 4) << 3);
            const uint32_t db = sbase + slot * SLOT_BYTES + wl * 2048 + krow * 128;
#pragma unroll
            for (int j = 0; j < 4; j++) ldsm4t(ad[j], db + (((2 * j + ((lane >> 3) & 1)) ^ (krow & 7)) << 4));
            bar_sync_p<6, NCONS + 64>(lv);
            uint32_t b[4];
            ldsm4(b, sa);
#pragma unroll
            for (int j = 0; j < 4; j++) {
                float acc[4] = {0.f, 0.f, 0.f, 0.f};
                mma16816(acc, ad[j], b[0], b[1]);
                st_tag2(p_in2 + (2 * j) * NFCTA * 16, acc[0], acc[1], tag, pw);
                st_tag2(p_in2 + (2 * j + 1) * NFCTA * 16, acc[2], acc[3], tag, pw);
            }
            bar_arrive_p<9, NALL>(lv);
        }
    }
    if (lv) return;

    {
        const int hw = (tid >> 5) - 9;
        const int red_b = 2 * (c >> 6) + ((lane >> 3) & 1);
        const int red_n = 8 * (c & 63) + 2 * t4 + ((lane >> 4) & 1);
        const float x_res = __bfloat162float(x[red_b * DM + red_n]);
        const int cta0 = (hw * 8 + (c >> 4)) * 4, hh = (c >> 2) & 3;
        const float* q_po = &g_po[(cta0 * 4 + hh) * DH + lane * 4];
        const float* q_pml = &g_pml[(cta0 * 4 + hh) * 2];
        const float* q_in1 = &g_in1[(c * 32 + r) * 16 + 4 * t4];
        float* p_h = &g_h[((lane & 4) ? HREP / 2 : 0) * (NB * DM) + red_b * DM + red_n];
        const float* q_h = &g_h[(c % HREP) * (NB * DM) + hw * DM + lane * 4];
        const float* q_in2 = &g_in2[(c * NFCTA + r) * 16 + 4 * t4];
        __nv_bfloat16* p_out = out + red_b * DM + red_n;
        uint32_t s_ofw = s_of + (hw * 136 + lane * 4) * 2, s_hn = s_xn + hw * 1040 + lane * 8;
        uint32_t s_gu = s_red + (((hw & 1) * 2 + (lane >> 4)) * 20 + (lane & 15)) * 4;
        uint32_t s_actw = s_act + (((hw & 1) * 2 + (lane >> 4)) * 24 + (lane & 15)) * 2;
        uint32_t s_fin = s_of + lane * 4;
        pin(s_fin);
        pin(q_po); pin(q_pml); pin(q_in1); pin(p_h); pin(q_h); pin(q_in2); pin(p_out); pin(s_ofw); pin(s_hn); pin(s_gu); pin(s_actw);

#pragma unroll 1
        for (int pass = 0; pass < 2; pass++) {
            asm volatile("mov.u32 %0, %1;" : "=r"(lv) : "r"(pass));
            if (lv) {
                if (hw == 0) {
                    uint32_t it = 0;
                    while (true) {
                        const int seen = (int)(ld_rlx1(&g_count) - epoch * NCTA);
                        if (lane == 0) asm volatile("st.volatile.shared.u32 [%0], %1;" ::"r"(sbase + SM_CNT), "r"(seen) : "memory");
                        if (seen >= NCTA) break;
                        __nanosleep(seen > 0 ? 100 : 1000);
                        if (++it > SPIN_LIMIT) __trap();
                    }
                }
                asm volatile("bar.sync 10, 128;" ::: "memory");
                asm volatile("bar.sync 11, 384;" ::: "memory");
                spin_cycles(POLL_DELAY1);
            }
            {
                PollSet<4, 4 * DH, 4, 8> ps;
                poll1(ps, q_po, q_pml, tag, lv);
                const uint4 (&ov)[4] = ps.v;
                const uint2 (&ml)[4] = ps.m;
                const float M = fmaxf(fmaxf(u2f(ml[0].x), u2f(ml[1].x)), fmaxf(u2f(ml[2].x), u2f(ml[3].x)));
                const float e0 = ex2((u2f(ml[0].x) - M) * LOG2E), e1 = ex2((u2f(ml[1].x) - M) * LOG2E);
                const float e2 = ex2((u2f(ml[2].x) - M) * LOG2E), e3 = ex2((u2f(ml[3].x) - M) * LOG2E);
                const float inv = rcp_approx(fmaf(e0, u2f(ml[0].y), e1 * u2f(ml[1].y)) + fmaf(e2, u2f(ml[2].y), e3 * u2f(ml[3].y)));
                const float a0 = fmaf(e0, u2f(ov[0].x), e1 * u2f(ov[1].x)) + fmaf(e2, u2f(ov[2].x), e3 * u2f(ov[3].x));
                const float a1 = fmaf(e0, u2f(ov[0].y), e1 * u2f(ov[1].y)) + fmaf(e2, u2f(ov[2].y), e3 * u2f(ov[3].y));
                const float a2 = fmaf(e0, u2f(ov[0].z), e1 * u2f(ov[1].z)) + fmaf(e2, u2f(ov[2].z), e3 * u2f(ov[3].z));
                const float a3 = fmaf(e0, u2f(ov[0].w), e1 * u2f(ov[1].w)) + fmaf(e2, u2f(ov[2].w), e3 * u2f(ov[3].w));
                sts64(s_ofw, pack_bf16(a0 * inv, a1 * inv), pack_bf16(a2 * inv, a3 * inv), lv);
                bar_arrive_p<3, NALL>(lv);
            }
            float h_res = 0.f;
            if (hw == 3 || !lv) {
                bar_sync_p<8, NCONS + 32>(lv);
                if (lv) spin_cycles(POLL_DELAY);
                const float kk = inbox_reduce<false>(q_in1, tag, lv, lane);
                h_res = bf16r(x_res + bf16r(kk));
#pragma unroll
                for (int rp = 0; rp < HREP / 2; rp++) st_tag1(p_h + rp * (NB * DM), h_res, tag, lv);
                bar_arrive_p<7, 128>(lv);
            }
            if (hw != 3) bar_sync_p<7, 128>(lv);
            if (lv) spin_cycles(POLL_DELAY);
            if (c < NFCTA) {
                PollSet<4, 128, 0, 0> ps;
                poll1(ps, q_h, q_h, tag, lv);
                const uint4 (&u)[4] = ps.v;
                float v[16];
#pragma unroll
                for (int k = 0; k < 4; k++) {
                    v[4 * k + 0] = u2f(u[k].x & 0xffff0000u); v[4 * k + 1] = u2f(u[k].y & 0xffff0000u);
                    v[4 * k + 2] = u2f(u[k].z & 0xffff0000u); v[4 * k + 3] = u2f(u[k].w & 0xffff0000u);
                }
                warp_layernorm_store(v, __shfl_sync(0xffffffffu, v[0], 0), s_hn, lv);
                bar_arrive_p<4, NALL>(lv);
                if (hw < 2 || !lv) {
                    bar_sync_p<5, NCONS + 64>(lv);
                    float gw[8], uw[8];
#pragma unroll
                    for (int w = 0; w < 8; w++) { gw[w] = lds32(s_gu + w * 640); uw[w] = lds32(s_gu + w * 640 + 320); }
                    const float g = bf16r(((gw[0] + gw[1]) + (gw[2] + gw[3])) + ((gw[4] + gw[5]) + (gw[6] + gw[7])));
                    const float u_ = bf16r(((uw[0] + uw[1]) + (uw[2] + uw[3])) + ((uw[4] + uw[5]) + (uw[6] + uw[7])));
                    const float inner = 0.7978845608028654f * fmaf(0.044715f * g * g, g, g);
                    const float ge = bf16r(__fdividef(g, 1.f + __expf(-2.f * inner)));
                    sts16(s_actw, __bfloat16_as_ushort(__float2bfloat16_rn(ge * u_)), lv);
                    bar_arrive_p<6, NCONS + 64>(lv);
                }
            }
            if (c < NFCTA) bar_sync_p<9, NALL>(lv);
            if (lv) spin_cycles(POLL_DELAY);
            const float k2p = inbox_reduce<true>(q_in2 + hw * 28 * 16, tag, lv, lane);
            sts32(s_fin + hw * 128, k2p, lv);
            if (hw != 3) bar_arrive_p<12, 128>(lv);
            if (hw == 3 || !lv) {
                bar_sync_p<12, 128>(lv);
                const float k2 = (lds32(s_fin) + lds32(s_fin + 128)) + (lds32(s_fin + 256) + lds32(s_fin + 384));
                if (lv && !(lane & 4)) *p_out = __float2bfloat16_rn(h_res + bf16r(k2));
                if (lv && c == 0 && lane == 0) {
                    asm volatile("st.relaxed.gpu.global.u32 [%0], %1;" ::"l"(&g_epoch), "r"(epoch + 1) : "memory");
                }
            }
        }
    }
}

typedef CUresult (*EncodeFn)(CUtensorMap*, CUtensorMapDataType, cuuint32_t, void*, const cuuint64_t*, const cuuint64_t*,
                             const cuuint32_t*, const cuuint32_t*, CUtensorMapInterleave, CUtensorMapSwizzle,
                             CUtensorMapL2promotion, CUtensorMapFloatOOBfill);

CUtensorMap make_map(EncodeFn enc, const void* base, int rank, const cuuint64_t* dims, const cuuint64_t* strides,
                     const cuuint32_t* box, CUtensorMapSwizzle sw, CUtensorMapL2promotion promo) {
    CUtensorMap tm;
    cuuint32_t es[3] = {1, 1, 1};
    enc(&tm, CU_TENSOR_MAP_DATA_TYPE_BFLOAT16, rank, const_cast<void*>(base), dims, strides, box, es,
        CU_TENSOR_MAP_INTERLEAVE_NONE, sw, promo, CU_TENSOR_MAP_FLOAT_OOB_FILL_NONE);
    return tm;
}

}

extern "C" void kernel_launch(void* const* d_in, const int* in_sizes, int n_in, void* d_out, int out_size) {
    (void)in_sizes; (void)n_in; (void)out_size;
    const void* x = d_in[0];
    const void* kc = d_in[1];
    const void* vc = d_in[2];
    const void* wq = d_in[3];
    const void* wo = d_in[4];
    const void* wg = d_in[6];
    const void* wu = d_in[7];
    const void* wd = d_in[8];

    static EncodeFn enc = nullptr;
    if (!enc) {
        void* fn = nullptr;
        cudaDriverEntryPointQueryResult qr;
        cudaGetDriverEntryPoint("cuTensorMapEncodeTiled", &fn, cudaEnableDefault, &qr);
        enc = reinterpret_cast<EncodeFn>(fn);
        cudaFuncSetAttribute(fused_decode_kernel, cudaFuncAttributeMaxDynamicSharedMemorySize, SMEM_BYTES);
    }
    const auto P256 = CU_TENSOR_MAP_L2_PROMOTION_L2_256B;
    CUtensorMap tmK, tmV, tmWq, tmWo, tmWg, tmWu, tmWd;
    {
        cuuint64_t dims[3] = {64, (cuuint64_t)NB * HKV * SK, 2};
        cuuint64_t str[2] = {256, 128};
        cuuint32_t box[3] = {64, 64, 2};
        tmK = make_map(enc, kc, 3, dims, str, box, CU_TENSOR_MAP_SWIZZLE_128B, P256);
        tmV = make_map(enc, vc, 3, dims, str, box, CU_TENSOR_MAP_SWIZZLE_128B, P256);
    }
    {
        cuuint64_t dims[2] = {HQ * DH, DM};
        cuuint64_t str[1] = {HQ * DH * 2};
        cuuint32_t box[2] = {32, 256};
        tmWq = make_map(enc, wq, 2, dims, str, box, CU_TENSOR_MAP_SWIZZLE_64B, P256);
    }
    {
        cuuint64_t dims[3] = {64, HQ * DH, 8};
        cuuint64_t str[2] = {DM * 2, 128};
        cuuint32_t box[3] = {64, 64, 1};
        tmWo = make_map(enc, wo, 3, dims, str, box, CU_TENSOR_MAP_SWIZZLE_128B, P256);
    }
    {
        cuuint64_t dims[2] = {FF, DM};
        cuuint64_t str[1] = {FF * 2};
        cuuint32_t box[2] = {16, 256};
        tmWg = make_map(enc, wg, 2, dims, str, box, CU_TENSOR_MAP_SWIZZLE_32B, P256);
        tmWu = make_map(enc, wu, 2, dims, str, box, CU_TENSOR_MAP_SWIZZLE_32B, P256);
    }
    {
        cuuint64_t dims[3] = {64, FF, 8};
        cuuint64_t str[2] = {DM * 2, 128};
        cuuint32_t box[3] = {64, 16, 4};
        tmWd = make_map(enc, wd, 3, dims, str, box, CU_TENSOR_MAP_SWIZZLE_128B, P256);
    }
    fused_decode_kernel<<<NCTA, NTHREADS, SMEM_BYTES, cudaStreamPerThread>>>(
        tmK, tmV, tmWq, tmWo, tmWg, tmWu, tmWd, (const __nv_bfloat16*)x, (__nv_bfloat16*)d_out);
}
```

```cpp
#include <cuda_runtime.h>
#include <cuda_bf16.h>
#include <cuda.h>
#include <stdint.h>

namespace {

constexpr int NB = 4, DM = 512, HQ = 32, HKV = 8, SK = 8192, DH = 128, FF = 1792;
constexpr int NCTA = 128;
constexpr int NSPLIT = 4;
constexpr int TILE = 256;
constexpr int NTILE = SK / NSPLIT / TILE;
constexpr int SLOT_BYTES = 16384;
constexpr int NSLOT = 12;
constexpr int ITEM_WO = 2 + 8 * NTILE;
constexpr int ITEM_GU = ITEM_WO + 2;
constexpr int ITEM_WD = ITEM_WO + 4;
constexpr int NFCTA = FF / 16;
constexpr int HREP = 4;
constexpr int NCONS = 256;
constexpr int NHELP = 4;
constexpr int NTHREADS = NCONS + 32 + 32 * NHELP;
constexpr int NALL = NCONS + 32 * NHELP;

constexpr int WINDOW = 4;
constexpr int WINDOW_EG = 5;
constexpr int EG_COUNT = 8;
constexpr int WINDOW_T = 4;
constexpr int TRIGGER = 96;
constexpr int POLL_DELAY1 = 300;
constexpr int POLL_DELAY = 450;
constexpr uint32_t SPIN_LIMIT = 1u << 22;

constexpr int SM_MRG = NSLOT * SLOT_BYTES;
constexpr int SM_ML = SM_MRG + 8 * 4 * 136 * 4;
constexpr int SM_XN = SM_ML + 8 * 4 * 2 * 4;
constexpr int SM_QS = SM_XN + 4 * 520 * 2;
constexpr int SM_OF = SM_QS + 4 * 136 * 2;
constexpr int SM_ACT = SM_OF + 4 * 136 * 2;
constexpr int SM_BAR = SM_ACT + 4 * 24 * 2;
constexpr int SM_CNT = SM_BAR + 2 * NSLOT * 8;
constexpr int SM_WBAR = SM_CNT + 16;
constexpr int SM_TOTAL = SM_WBAR + 80;
constexpr int SMEM_BYTES = SM_TOTAL + 1024;

__device__ unsigned g_epoch;
__device__ unsigned g_count;
__device__ __align__(128) float g_q[NB * HQ * DH];
__device__ __align__(128) float g_po[NCTA * 4 * DH];
__device__ __align__(128) float g_pml[NCTA * 4 * 2];
__device__ __align__(128) float g_in1[NCTA * 32 * 16];
__device__ __align__(128) float g_h[HREP * NB * DM];
__device__ __align__(128) float g_in2[NCTA * NFCTA * 16];

__device__ __forceinline__ uint32_t smem_u32(const void* p) { return (uint32_t)__cvta_generic_to_shared(p); }
__device__ __forceinline__ void mbar_init(uint32_t bar, uint32_t cnt) {
    asm volatile("mbarrier.init.shared::cta.b64 [%0], %1;" ::"r"(bar), "r"(cnt) : "memory");
}
__device__ __forceinline__ void mbar_expect_tx(uint32_t bar, uint32_t bytes) {
    asm volatile("mbarrier.arrive.expect_tx.shared::cta.b64 _, [%0], %1;" ::"r"(bar), "r"(bytes) : "memory");
}
__device__ __forceinline__ void mbar_arrive(uint32_t bar) {
    asm volatile("mbarrier.arrive.shared::cta.b64 _, [%0];" ::"r"(bar) : "memory");
}
__device__ __forceinline__ void mbar_wait(uint32_t bar, uint32_t parity) {
    uint32_t done = 0, it = 0;
    while (true) {
        asm volatile("{\n.reg .pred p;\nmbarrier.try_wait.parity.shared::cta.b64 p, [%1], %2;\nselp.u32 %0, 1, 0, p;\n}"
                     : "=r"(done) : "r"(bar), "r"(parity) : "memory");
        if (done) break;
        if (++it > SPIN_LIMIT) __trap();
    }
}
__device__ __forceinline__ void mbar_wait_p(uint32_t bar, uint32_t parity, uint32_t lv) {
    uint32_t it = 0;
    while (true) {
        uint32_t done;
        asm volatile("{\n.reg .pred p, q;\nsetp.ne.u32 q, %3, 0;\nsetp.eq.u32 p, %3, 0;\n"
                     "@q mbarrier.try_wait.parity.shared::cta.b64 p, [%1], %2;\nselp.u32 %0, 1, 0, p;\n}"
                     : "=r"(done) : "r"(bar), "r"(parity), "r"(lv) : "memory");
        if (done) break;
        if (++it > SPIN_LIMIT) __trap();
    }
}
__device__ __forceinline__ void tma2d(uint32_t dst, const CUtensorMap* tm, int c0, int c1, uint32_t bar, uint64_t pol) {
    asm volatile("cp.async.bulk.tensor.2d.shared::cluster.global.mbarrier::complete_tx::bytes.L2::cache_hint [%0], [%1, {%3, %4}], [%2], %5;"
                 ::"r"(dst), "l"(tm), "r"(bar), "r"(c0), "r"(c1), "l"(pol) : "memory");
}
__device__ __forceinline__ void tma3d(uint32_t dst, const CUtensorMap* tm, int c0, int c1, int c2, uint32_t bar, uint64_t pol) {
    asm volatile("cp.async.bulk.tensor.3d.shared::cluster.global.mbarrier::complete_tx::bytes.L2::cache_hint [%0], [%1, {%3, %4, %5}], [%2], %6;"
                 ::"r"(dst), "l"(tm), "r"(bar), "r"(c0), "r"(c1), "r"(c2), "l"(pol) : "memory");
}
__device__ __forceinline__ void tm_prefetch(const CUtensorMap* tm) {
    asm volatile("prefetch.tensormap [%0];" ::"l"(tm) : "memory");
}
__device__ __forceinline__ void ldsm4(uint32_t (&r)[4], uint32_t addr) {
    asm volatile("ldmatrix.sync.aligned.m8n8.x4.shared.b16 {%0,%1,%2,%3}, [%4];"
                 : "=r"(r[0]), "=r"(r[1]), "=r"(r[2]), "=r"(r[3]) : "r"(addr) : "memory");
}
__device__ __forceinline__ void ldsm4t(uint32_t (&r)[4], uint32_t addr) {
    asm volatile("ldmatrix.sync.aligned.m8n8.x4.trans.shared.b16 {%0,%1,%2,%3}, [%4];"
                 : "=r"(r[0]), "=r"(r[1]), "=r"(r[2]), "=r"(r[3]) : "r"(addr) : "memory");
}
__device__ __forceinline__ void mma16816(float (&c)[4], const uint32_t (&a)[4], uint32_t b0, uint32_t b1) {
    asm volatile("mma.sync.aligned.m16n8k16.row.col.f32.bf16.bf16.f32 {%0,%1,%2,%3}, {%4,%5,%6,%7}, {%8,%9}, {%0,%1,%2,%3};"
                 : "+f"(c[0]), "+f"(c[1]), "+f"(c[2]), "+f"(c[3])
                 : "r"(a[0]), "r"(a[1]), "r"(a[2]), "r"(a[3]), "r"(b0), "r"(b1));
}
__device__ __forceinline__ uint32_t movm_t(uint32_t a) {
    uint32_t d;
    asm volatile("movmatrix.sync.aligned.m8n8.trans.b16 %0, %1;" : "=r"(d) : "r"(a));
    return d;
}
__device__ __forceinline__ uint32_t pack_bf16(float lo, float hi) {
    uint32_t d;
    asm("cvt.rn.bf16x2.f32 %0, %1, %2;" : "=r"(d) : "f"(hi), "f"(lo));
    return d;
}
__device__ __forceinline__ float bf16r(float x) { return __bfloat162float(__float2bfloat16_rn(x)); }
__device__ __forceinline__ float bf_lo(uint32_t w) { return __uint_as_float(w << 16); }
__device__ __forceinline__ float bf_hi(uint32_t w) { return __uint_as_float(w & 0xffff0000u); }
__device__ __forceinline__ float ex2(float x) {
    float y;
    asm("ex2.approx.ftz.f32 %0, %1;" : "=f"(y) : "f"(x));
    return y;
}
__device__ __forceinline__ void cons_sync() { asm volatile("bar.sync 1, 256;" ::: "memory"); }
template <int ID, int CNT> __device__ __forceinline__ void bar_sync_p(uint32_t lv) {
    asm volatile("{\n.reg .pred q;\nsetp.ne.u32 q, %0, 0;\n@q bar.sync %1, %2;\n}" ::"r"(lv), "n"(ID), "n"(CNT) : "memory");
}
template <int ID, int CNT> __device__ __forceinline__ void bar_arrive_p(uint32_t lv) {
    asm volatile("{\n.reg .pred q;\nsetp.ne.u32 q, %0, 0;\n@q bar.arrive %1, %2;\n}" ::"r"(lv), "n"(ID), "n"(CNT) : "memory");
}
__device__ __forceinline__ void spin_cycles(uint32_t n) {
    const uint32_t t0 = (uint32_t)clock();
    while ((uint32_t)clock() - t0 < n) {}
}
__device__ __forceinline__ void sts32(uint32_t a, float v, uint32_t p) {
    asm volatile("{\n.reg .pred q;\nsetp.ne.u32 q, %2, 0;\n@q st.shared.f32 [%0], %1;\n}" ::"r"(a), "f"(v), "r"(p) : "memory");
}
__device__ __forceinline__ void sts16(uint32_t a, uint16_t v, uint32_t p) {
    asm volatile("{\n.reg .pred q;\nsetp.ne.u32 q, %2, 0;\n@q st.shared.u16 [%0], %1;\n}" ::"r"(a), "h"(v), "r"(p) : "memory");
}
__device__ __forceinline__ void sts64(uint32_t a, uint32_t x, uint32_t y, uint32_t p) {
    asm volatile("{\n.reg .pred q;\nsetp.ne.u32 q, %3, 0;\n@q st.shared.v2.u32 [%0], {%1, %2};\n}" ::"r"(a), "r"(x), "r"(y), "r"(p) : "memory");
}
__device__ __forceinline__ float lds32(uint32_t a) {
    float v; asm volatile("ld.shared.f32 %0, [%1];" : "=f"(v) : "r"(a) : "memory"); return v;
}
__device__ __forceinline__ float2 lds64(uint32_t a) {
    float2 v; asm volatile("ld.shared.v2.f32 {%0, %1}, [%2];" : "=f"(v.x), "=f"(v.y) : "r"(a) : "memory"); return v;
}

__device__ __forceinline__ float u2f(uint32_t u) { return __uint_as_float(u); }
__device__ __forceinline__ float untag(uint32_t u) { return __uint_as_float(u & ~1u); }
__device__ __forceinline__ float tagf(float v, uint32_t tag) { return __uint_as_float((__float_as_uint(v) & ~1u) | tag); }
__device__ __forceinline__ void st_tag1(float* ptr, float v, uint32_t tag, uint32_t p) {
    asm volatile("{\n.reg .pred q;\nsetp.ne.u32 q, %2, 0;\n@q st.relaxed.gpu.global.f32 [%0], %1;\n}"
                 ::"l"(ptr), "f"(tagf(v, tag)), "r"(p) : "memory");
}
__device__ __forceinline__ void st_tag2(float* ptr, float a, float b, uint32_t tag, uint32_t p) {
    asm volatile("{\n.reg .pred q;\nsetp.ne.u32 q, %3, 0;\n@q st.relaxed.gpu.global.v2.f32 [%0], {%1, %2};\n}"
                 ::"l"(ptr), "f"(tagf(a, tag)), "f"(tagf(b, tag)), "r"(p) : "memory");
}
__device__ __forceinline__ void ld_rlx4(uint4& v, const float* ptr, uint32_t p) {
    asm volatile("{\n.reg .pred q;\nsetp.ne.u32 q, %5, 0;\n@q ld.relaxed.gpu.global.v4.u32 {%0,%1,%2,%3}, [%4];\n}"
                 : "+r"(v.x), "+r"(v.y), "+r"(v.z), "+r"(v.w) : "l"(ptr), "r"(p) : "memory");
}
__device__ __forceinline__ void ld_rlx2(uint2& v, const float* ptr, uint32_t p) {
    asm volatile("{\n.reg .pred q;\nsetp.ne.u32 q, %3, 0;\n@q ld.relaxed.gpu.global.v2.u32 {%0,%1}, [%2];\n}"
                 : "+r"(v.x), "+r"(v.y) : "l"(ptr), "r"(p) : "memory");
}
__device__ __forceinline__ uint32_t ld_rlx1(const unsigned* p) {
    uint32_t v;
    asm volatile("ld.relaxed.gpu.global.u32 %0, [%1];" : "=r"(v) : "l"(p) : "memory");
    return v;
}
__device__ __forceinline__ uint32_t bad4(const uint4& v, uint32_t tag) {
    uint32_t u, w, r;
    asm("lop3.b32 %0, %1, %2, %3, 0x7E;" : "=r"(u) : "r"(v.x), "r"(v.y), "r"(tag));
    asm("lop3.b32 %0, %1, %2, %3, 0x7E;" : "=r"(w) : "r"(v.z), "r"(v.w), "r"(tag));
    asm("lop3.b32 %0, %1, %2, 1, 0xA8;" : "=r"(r) : "r"(u), "r"(w));
    return r;
}
__device__ __forceinline__ uint32_t bad2(const uint2& v, uint32_t tag) {
    uint32_t u;
    asm("lop3.b32 %0, %1, %2, %3, 0x7E;" : "=r"(u) : "r"(v.x), "r"(v.y), "r"(tag));
    return u & 1u;
}
template <typename T> __device__ __forceinline__ void pin(T*& p) { asm volatile("" : "+l"(p)); }
__device__ __forceinline__ void pin(uint32_t& v) { asm volatile("" : "+r"(v)); }
__device__ __forceinline__ float sqrt_approx(float x) { float y; asm("sqrt.approx.ftz.f32 %0, %1;" : "=f"(y) : "f"(x)); return y; }
__device__ __forceinline__ float rcp_approx(float x) { float y; asm("rcp.approx.ftz.f32 %0, %1;" : "=f"(y) : "f"(x)); return y; }
template <int NK, int KS, int NM, int MS>
struct PollSet {
    uint4 v[NK]; uint2 m[NM > 0 ? NM : 1]; uint32_t bad[NK], badm[NM > 0 ? NM : 1];
    __device__ __forceinline__ void init(uint32_t tag, uint32_t lv) {
#pragma unroll
        for (int k = 0; k < NK; k++) { v[k] = make_uint4(tag, tag, tag, tag); bad[k] = lv; }
#pragma unroll
        for (int k = 0; k < NM; k++) { m[k] = make_uint2(tag, tag); badm[k] = lv; }
    }
    __device__ __forceinline__ void issue(const float* src, const float* src2) {
#pragma unroll
        for (int k = 0; k < NK; k++) ld_rlx4(v[k], src + k * KS, bad[k]);
#pragma unroll
        for (int k = 0; k < NM; k++) ld_rlx2(m[k], src2 + k * MS, badm[k]);
    }
    __device__ __forceinline__ bool complete(uint32_t tag) {
        uint32_t any = 0;
#pragma unroll
        for (int k = 0; k < NK; k++) { bad[k] = bad4(v[k], tag); any |= bad[k]; }
#pragma unroll
        for (int k = 0; k < NM; k++) { badm[k] = bad2(m[k], tag); any |= badm[k]; }
        return !__any_sync(0xffffffffu, any);
    }
};
constexpr float LOG2E = 1.4426950408889634f;

__device__ __forceinline__ void warp_layernorm_store(const float (&v)[16], float c, uint32_t dst, uint32_t p) {
    float s1[4], s2[4];
#pragma unroll
    for (int k = 0; k < 4; k++) {
        const float d0 = v[4 * k] - c, d1 = v[4 * k + 1] - c, d2 = v[4 * k + 2] - c, d3 = v[4 * k + 3] - c;
        s1[k] = (d0 + d1) + (d2 + d3);
        s2[k] = fmaf(d0, d0, d1 * d1) + fmaf(d2, d2, d3 * d3);
    }
    float t1 = (s1[0] + s1[1]) + (s1[2] + s1[3]), t2 = (s2[0] + s2[1]) + (s2[2] + s2[3]);
#pragma unroll
    for (int o = 16; o > 0; o >>= 1) {
        t1 += __shfl_xor_sync(0xffffffffu, t1, o);
        t2 += __shfl_xor_sync(0xffffffffu, t2, o);
    }
    const float md = t1 * (1.f / 512.f);
    const float mean = bf16r(c + md);
    const float var = bf16r(fmaxf(fmaf(-md, md, t2 * (1.f / 512.f)), 0.f));
    const float inv = rcp_approx(bf16r(sqrt_approx(bf16r(var + 1e-5f))));
#pragma unroll
    for (int k = 0; k < 4; k++) {
        const uint32_t t01 = pack_bf16(v[4 * k + 0] - mean, v[4 * k + 1] - mean);
        const uint32_t t23 = pack_bf16(v[4 * k + 2] - mean, v[4 * k + 3] - mean);
        sts64(dst + k * 256, pack_bf16(bf_lo(t01) * inv, bf_hi(t01) * inv), pack_bf16(bf_lo(t23) * inv, bf_hi(t23) * inv), p);
    }
}

template <class PS>
__device__ __forceinline__ void poll1(PS& ps, const float* src, const float* src2, uint32_t tag, uint32_t lv) {
    ps.init(tag, lv);
    uint32_t it = 0;
    while (true) {
        ps.issue(src, src2);
        if (ps.complete(tag)) break;
        if (++it > SPIN_LIMIT) __trap();
    }
}
template <bool PART>
__device__ __forceinline__ float inbox_reduce(const float* src, uint32_t tag, uint32_t lv, int lane) {
    PollSet<4, 128, 0, 0> ps;
    ps.init(tag, lv);
    const bool last = !PART || (lane >> 2) < 4;
    if (!last) ps.bad[3] = 0;
    uint32_t it = 0;
    while (true) {
        ps.issue(src, src);
        if (ps.complete(tag)) break;
        if (++it > SPIN_LIMIT) __trap();
    }
    const float m3 = last ? 1.f : 0.f;
    const float a = (untag(ps.v[0].x) + untag(ps.v[1].x)) + fmaf(m3, untag(ps.v[3].x), untag(ps.v[2].x));
    const float b = (untag(ps.v[0].y) + untag(ps.v[1].y)) + fmaf(m3, untag(ps.v[3].y), untag(ps.v[2].y));
    const float c = (untag(ps.v[0].z) + untag(ps.v[1].z)) + fmaf(m3, untag(ps.v[3].z), untag(ps.v[2].z));
    const float d = (untag(ps.v[0].w) + untag(ps.v[1].w)) + fmaf(m3, untag(ps.v[3].w), untag(ps.v[2].w));
    const bool hi = lane & 16, h2 = lane & 8;
    float k0 = hi ? c : a, k1 = hi ? d : b;
    k0 += __shfl_xor_sync(0xffffffffu, hi ? a : c, 16);
    k1 += __shfl_xor_sync(0xffffffffu, hi ? b : d, 16);
    float kk = h2 ? k1 : k0;
    kk += __shfl_xor_sync(0xffffffffu, h2 ? k0 : k1, 8);
    kk += __shfl_xor_sync(0xffffffffu, kk, 4);
    return kk;
}


__global__ void __launch_bounds__(NTHREADS, 1)
fused_decode_kernel(const __grid_constant__ CUtensorMap tmK, const __grid_constant__ CUtensorMap tmV,
                    const __grid_constant__ CUtensorMap tmWq, const __grid_constant__ CUtensorMap tmWo,
                    const __grid_constant__ CUtensorMap tmWg, const __grid_constant__ CUtensorMap tmWu,
                    const __grid_constant__ CUtensorMap tmWd,
                    const __nv_bfloat16* __restrict__ x, __nv_bfloat16* __restrict__ out) {
    extern __shared__ uint8_t smem_raw[];
    const uint32_t sbase = (smem_u32(smem_raw) + 1023u) & ~1023u;
    const uint32_t bar_full = sbase + SM_BAR, bar_empty = bar_full + NSLOT * 8;
    const int tid = threadIdx.x, lane = tid & 31;
    const int c = blockIdx.x;
    const int row0 = (c >> 2) * SK + (c & 3) * (SK / NSPLIT);
    uint64_t pol_stream = 0;
    if (tid == NCONS) {
        tm_prefetch(&tmWq); tm_prefetch(&tmK); tm_prefetch(&tmV);
        for (int i = 0; i < 4; i++) mbar_init(bar_full + 8 * i, 1);
        asm volatile("fence.proxy.async.shared::cta;" ::: "memory");
        asm volatile("createpolicy.fractional.L2::evict_first.b64 %0, 1.0;" : "=l"(pol_stream));
        mbar_expect_tx(bar_full, SLOT_BYTES);
        tma2d(sbase, &tmWq, 32 * c, 0, bar_full, pol_stream);
        mbar_expect_tx(bar_full + 8, SLOT_BYTES);
        tma2d(sbase + SLOT_BYTES, &tmWq, 32 * c, 256, bar_full + 8, pol_stream);
        mbar_expect_tx(bar_full + 16, SLOT_BYTES);
        tma3d(sbase + 2 * SLOT_BYTES, &tmK, 0, row0, 0, bar_full + 16, pol_stream);
        mbar_expect_tx(bar_full + 24, SLOT_BYTES);
        tma3d(sbase + 3 * SLOT_BYTES, &tmK, 0, row0 + 64, 0, bar_full + 24, pol_stream);
        for (int i = 4; i < NSLOT; i++) mbar_init(bar_full + 8 * i, 1);
        for (int i = 0; i < NSLOT; i++) mbar_init(bar_empty + 8 * i, 4);
        for (int i = 0; i < 10; i++) mbar_init(sbase + SM_WBAR + 8 * i, 1);
        asm volatile("fence.proxy.async.shared::cta;" ::: "memory");
        asm volatile("st.volatile.shared.u32 [%0], %1;" ::"r"(sbase + SM_CNT), "r"(0) : "memory");
    }
    __syncthreads();

    if ((tid >> 5) == 8) {
        if (lane == 0) {
            auto acquire = [&](int i, int window) {
                if (i >= NSLOT) mbar_wait(bar_empty + 8 * (i % NSLOT), ((i / NSLOT) - 1) & 1);
                if (i >= window) { const int j = i - window; mbar_wait(bar_full + 8 * (j % NSLOT), (j / NSLOT) & 1); }
            };
            auto seen_count = [&]() {
                uint32_t seen;
                asm volatile("ld.volatile.shared.u32 %0, [%1];" : "=r"(seen) : "r"(sbase + SM_CNT) : "memory");
                return (int)seen;
            };
#pragma unroll 1
            for (int i = 4; i < ITEM_WO; i++) {
                const int slot = i % NSLOT;
                acquire(i, (i >= ITEM_WO - 24 && seen_count() >= EG_COUNT) ? WINDOW_EG : WINDOW);
                mbar_expect_tx(bar_full + 8 * slot, SLOT_BYTES);
                tma3d(sbase + slot * SLOT_BYTES, (((i - 2) >> 2) & 1) ? &tmV : &tmK, 0, row0 + ((i - 2) >> 3) * TILE + ((i - 2) & 3) * 64, 0,
                      bar_full + 8 * slot, pol_stream);
            }
            asm volatile("red.relaxed.gpu.global.add.u32 [%0], 1;" ::"l"(&g_count) : "memory");
            tm_prefetch(&tmWo); tm_prefetch(&tmWg); tm_prefetch(&tmWu); tm_prefetch(&tmWd);
            {
                uint32_t it = 0;
                while (seen_count() < TRIGGER) {
                    __nanosleep(20);
                    if (++it > SPIN_LIMIT) __trap();
                }
            }
            const int npiece = (c < NFCTA) ? 10 : 4;
#pragma unroll 1
            for (int j = 0; j < npiece; j++) {
                const int item = j < 4 ? ITEM_WO + (j >> 1) : (j < 8 ? ITEM_GU + ((j - 4) >> 1) : ITEM_WD + (j - 8));
                const int slot = item % NSLOT;
                mbar_wait(bar_empty + 8 * slot, ((item / NSLOT) - 1) & 1);
                if (j >= WINDOW_T) mbar_wait(sbase + SM_WBAR + 8 * (j - WINDOW_T), 0);
                else if (j < 2) { const int jj = ITEM_WO - 2 + j; mbar_wait(bar_full + 8 * (jj % NSLOT), (jj / NSLOT) & 1); }
                const uint32_t fb = sbase + SM_WBAR + 8 * j, dst = sbase + slot * SLOT_BYTES + ((j < 8) ? (j & 1) * 8192 : 0);
                mbar_expect_tx(fb, 8192);
                if (j < 4) tma3d(dst, &tmWo, 0, 128 * (c >> 2) + 64 * (j & 1), 2 * (c & 3) + (j >> 1), fb, pol_stream);
                else if (j < 8) tma2d(dst, (j & 1) ? &tmWu : &tmWg, 16 * c, 256 * ((j - 4) >> 1), fb, pol_stream);
                else tma3d(dst, &tmWd, 0, 16 * c, 4 * (j - 8), fb, pol_stream);
            }
        }
        return;
    }

    uint32_t lv;
    asm volatile("mov.u32 %0, %1;" : "=r"(lv) : "r"((tid < NCONS) ? 1u : 0u));
    const int warp = lv ? (tid >> 5) : 0;
    const int vtid = warp * 32 + lane;
    const int r = lane >> 2, t4 = lane & 3;
    const int wg = warp >> 2, wl = warp & 3;
    const uint32_t s_red = sbase + SM_MRG, s_ml = sbase + SM_ML, s_xn = sbase + SM_XN;
    const uint32_t s_qs = sbase + SM_QS, s_of = sbase + SM_OF, s_act = sbase + SM_ACT;
    const int brow = lane & 3, bch = lane >> 3;

    uint2 xw[4];
#pragma unroll
    for (int k = 0; k < 4; k++) {
        xw[k] = make_uint2(0u, 0u);
        asm volatile("{\n.reg .pred q;\nsetp.ne.u32 q, %3, 0;\n@q ld.global.nc.v2.u32 {%0, %1}, [%2];\n}"
                     : "+r"(xw[k].x), "+r"(xw[k].y) : "l"(x + (warp & 3) * DM + k * 128 + lane * 4), "r"((uint32_t)(lv && warp < NB)));
    }
    const unsigned epoch = ld_rlx1(&g_epoch);
    uint32_t tag = 0;

    float* p_po = &g_po[(c * 4 + (vtid >> 6)) * DH + (vtid & 63) * 2];
    float* p_pml = &g_pml[(c * 4 + (vtid >> 6)) * 2];
    float* p_in1 = &g_in1[((t4 * 64 + 16 * (c & 3) + 2 * warp) * 32 + (c >> 2)) * 16 + 2 * r];
    float* p_in2 = &g_in2[((t4 * 64 + 8 * warp) * NFCTA + (c < NFCTA ? c : 0)) * 16 + 2 * r];
    pin(p_po); pin(p_pml); pin(p_in1); pin(p_in2);

    float o[8][4];
#pragma unroll
    for (int j = 0; j < 8; j++) { o[j][0] = o[j][1] = o[j][2] = o[j][3] = 0.f; }
    float mfin0 = 0.f, mfin1 = 0.f;

    if (lv) {
        if (warp < NB) {
            float v[16];
#pragma unroll
            for (int k = 0; k < 4; k++) {
                const uint2 w = xw[k];
                v[4 * k + 0] = bf_lo(w.x); v[4 * k + 1] = bf_hi(w.x); v[4 * k + 2] = bf_lo(w.y); v[4 * k + 3] = bf_hi(w.y);
            }
            warp_layernorm_store(v, __shfl_sync(0xffffffffu, v[0], 0), s_xn + warp * 1040 + lane * 8, 1u);
        }
        cons_sync();
        asm volatile("lop3.b32 %0, %1, 1, 1, 0x6A;" : "=r"(tag) : "r"(epoch));

        mbar_wait(bar_full + 8 * wg, 0);
        {
            float acc[2][4] = {};
#pragma unroll
            for (int kp = 0; kp < 2; kp++) {
                uint32_t b[4];
                ldsm4(b, s_xn + brow * 1040 + (warp * 64 + kp * 32 + bch * 8) * 2);
#pragma unroll
                for (int k2 = 0; k2 < 2; k2++) {
                    const int krow = warp * 64 + kp * 32 + k2 * 16 + (lane & 7) + ((lane >> 4) << 3);
#pragma unroll
                    for (int mt = 0; mt < 2; mt++) {
                        const int chunk = mt * 2 + ((lane >> 3) & 1);
                        uint32_t a[4];
                        ldsm4t(a, sbase + krow * 64 + ((chunk ^ ((krow >> 1) & 3)) << 4));
                        mma16816(acc[mt], a, b[2 * k2], b[2 * k2 + 1]);
                    }
                }
            }
            __syncwarp();
            if (lane == 0) mbar_arrive(bar_empty + 8 * wg);
            const uint32_t pq = t4 < 2;
#pragma unroll
            for (int mt = 0; mt < 2; mt++) {
                const uint32_t dst = s_red + (warp * 144 + (2 * t4) * 36 + mt * 16 + r) * 4;
                sts32(dst, acc[mt][0], pq); sts32(dst + 144, acc[mt][1], pq);
                sts32(dst + 32, acc[mt][2], pq); sts32(dst + 144 + 32, acc[mt][3], pq);
            }
            cons_sync();
            if (tid < 128) {
                float s = 0.f;
#pragma unroll
                for (int w = 0; w < 8; w++) s += lds32(s_red + (w * 144 + warp * 36 + lane) * 4);
                st_tag1(&g_q[warp * (HQ * DH) + 32 * c + lane], bf16r(s), tag, 1u);
                const int g = c >> 2;
                const float* src = &g_q[(g >> 3) * (HQ * DH) + (g & 7) * 512 + tid * 4];
                uint4 v;
                uint32_t it = 0;
                while (true) {
                    ld_rlx4(v, src, 1u);
                    if (!(bad4(v, tag) & 1)) break;
                    if (++it > SPIN_LIMIT) __trap();
                }
                sts64(s_qs + (warp * 136 + lane * 4) * 2, (v.x >> 16) | (v.y & 0xffff0000u), (v.z >> 16) | (v.w & 0xffff0000u), 1u);
            }
            cons_sync();
        }

        uint32_t qf[8][2];
#pragma unroll
        for (int j = 0; j < 8; j += 2) {
            uint32_t b[4];
            ldsm4(b, s_qs + brow * 272 + (j * 16 + bch * 8) * 2);
            qf[j][0] = b[0]; qf[j][1] = b[1]; qf[j + 1][0] = b[2]; qf[j + 1][1] = b[3];
        }
        const int krow = wl * 16 + (lane & 7) + (((lane >> 3) & 1) << 3);
        const int kch = lane >> 4;
        const int vrow = wl * 16 + (lane & 7) + ((lane >> 4) << 3);
        const int vch = (lane >> 3) & 1;
        const float scale = 0.08838834764831845f;
        float m0 = -INFINITY, m1 = -INFINITY, l0 = 0.f, l1 = 0.f;

#pragma unroll 1
        for (int t = 0; t < NTILE; t++) {
            float sc[2][4];
#pragma unroll
            for (int a = 0; a < 2; a++) {
                const int ik = 2 + 8 * t + 2 * a + wg;
                const int sk = ik % NSLOT;
                mbar_wait(bar_full + 8 * sk, (ik / NSLOT) & 1);
                float sa[4] = {0.f, 0.f, 0.f, 0.f}, sb[4] = {0.f, 0.f, 0.f, 0.f};
                const uint32_t kb = sbase + sk * SLOT_BYTES + krow * 128;
#pragma unroll
                for (int j = 0; j < 8; j += 2) {
                    uint32_t a0[4], a1[4];
                    ldsm4(a0, kb + (j >> 2) * 8192 + (((((j & 3) << 1) + kch) ^ (krow & 7)) << 4));
                    ldsm4(a1, kb + ((j + 1) >> 2) * 8192 + ((((((j + 1) & 3) << 1) + kch) ^ (krow & 7)) << 4));
                    mma16816(sa, a0, qf[j][0], qf[j][1]);
                    mma16816(sb, a1, qf[j + 1][0], qf[j + 1][1]);
                }
                __syncwarp();
                if (lane == 0) mbar_arrive(bar_empty + 8 * sk);
#pragma unroll
                for (int e = 0; e < 4; e++) sc[a][e] = bf16r(bf16r(sa[e] + sb[e]) * scale);
            }
            float x0 = fmaxf(fmaxf(fmaxf(sc[0][0], sc[0][2]), fmaxf(sc[1][0], sc[1][2])), m0);
            float x1 = fmaxf(fmaxf(fmaxf(sc[0][1], sc[0][3]), fmaxf(sc[1][1], sc[1][3])), m1);
#pragma unroll
            for (int off = 4; off < 32; off <<= 1) {
                x0 = fmaxf(x0, __shfl_xor_sync(0xffffffffu, x0, off));
                x1 = fmaxf(x1, __shfl_xor_sync(0xffffffffu, x1, off));
            }
            if (t == NTILE - 1) {
                sts64(s_ml + (warp * 4 + t4 * 2) * 4, __float_as_uint(x0), __float_as_uint(x1), r == 0 && t4 < 2);
                cons_sync();
#pragma unroll
                for (int w = 0; w < 8; w++) {
                    const float2 mw = lds64(s_ml + (w * 4 + (t4 & 1) * 2) * 4);
                    x0 = fmaxf(x0, mw.x); x1 = fmaxf(x1, mw.y);
                }
            }
            if (__any_sync(0xffffffffu, (x0 > m0) || (x1 > m1))) {
                const float a0 = ex2((m0 - x0) * LOG2E), a1 = ex2((m1 - x1) * LOG2E);
                m0 = x0; m1 = x1;
                l0 *= a0; l1 *= a1;
#pragma unroll
                for (int j = 0; j < 8; j++) { o[j][0] *= a0; o[j][1] *= a1; o[j][2] *= a0; o[j][3] *= a1; }
            }
            uint32_t pb[2][2];
#pragma unroll
            for (int a = 0; a < 2; a++) {
                const float p0 = ex2((sc[a][0] - m0) * LOG2E), p1 = ex2((sc[a][1] - m1) * LOG2E);
                const float p2 = ex2((sc[a][2] - m0) * LOG2E), p3 = ex2((sc[a][3] - m1) * LOG2E);
                l0 += p0 + p2; l1 += p1 + p3;
                pb[a][0] = movm_t(pack_bf16(p0, p1));
                pb[a][1] = movm_t(pack_bf16(p2, p3));
            }
            if (t == NTILE - 1) {
#pragma unroll
                for (int off = 4; off < 32; off <<= 1) {
                    l0 += __shfl_xor_sync(0xffffffffu, l0, off);
                    l1 += __shfl_xor_sync(0xffffffffu, l1, off);
                }
                sts64(s_ml + 128 + (warp * 4 + t4 * 2) * 4, __float_as_uint(l0), __float_as_uint(l1), r == 0 && t4 < 2);
            }
#pragma unroll
            for (int a = 0; a < 2; a++) {
                const int iv = 2 + 8 * t + 4 + 2 * a + wg;
                const int sv = iv % NSLOT;
                mbar_wait(bar_full + 8 * sv, (iv / NSLOT) & 1);
                const uint32_t vb = sbase + sv * SLOT_BYTES + vrow * 128;
#pragma unroll
                for (int j = 0; j < 8; j++) {
                    uint32_t av[4];
                    ldsm4t(av, vb + (j >> 2) * 8192 + (((((j & 3) << 1) + vch) ^ (vrow & 7)) << 4));
                    mma16816(o[j], av, pb[a][0], pb[a][1]);
                }
                __syncwarp();
                if (lane == 0) mbar_arrive(bar_empty + 8 * sv);
            }
        }
        mfin0 = m0; mfin1 = m1;
    } else {
        tag = (epoch & 1u) ^ 1u;
        __nanosleep(6000);
        const int wt = tid - (NCONS + 32);
        const float z = __uint_as_float(tag ^ 1u);
        auto st4 = [&](float* p) {
            asm volatile("st.relaxed.gpu.global.v4.f32 [%0], {%1, %1, %1, %1};" ::"l"(p), "f"(z) : "memory");
        };
        st4(&g_po[c * 512 + wt * 4]);
        st4(&g_in1[((((wt >> 2) >> 4) * 64 + 16 * (c & 3) + ((wt >> 2) & 15)) * 32 + (c >> 2)) * 16 + (wt & 3) * 4]);
        if (c < NFCTA)
            for (int i = wt; i < 512; i += 128) st4(&g_in2[((i >> 2) * NFCTA + c) * 16 + (i & 3) * 4]);
        if (wt < 16) st4(&g_h[(wt >> 2) * (NB * DM) + (2 * (c >> 6) + ((wt >> 1) & 1)) * DM + 8 * (c & 63) + (wt & 1) * 4]);
        else if (wt < 18) st4(&g_pml[c * 8 + (wt - 16) * 4]);
        asm volatile("bar.arrive 2, %0;" ::"n"(NALL) : "memory");
    }

    const uint32_t pw = lv && (t4 < 2);
    {
        const uint32_t dst = s_red + (warp * 544 + (2 * t4) * 136 + r) * 4;
#pragma unroll
        for (int j = 0; j < 8; j++) {
            sts32(dst + j * 64, o[j][0], pw);
            sts32(dst + 544 + j * 64, o[j][1], pw);
            sts32(dst + j * 64 + 32, o[j][2], pw);
            sts32(dst + 544 + j * 64 + 32, o[j][3], pw);
        }
        const int h = vtid >> 6;
        const uint32_t src = s_red + (h * 136 + (vtid & 63) * 2) * 4;
        const float Mh = __shfl_sync(0xffffffffu, (h & 1) ? mfin1 : mfin0, h >> 1);
        bar_sync_p<2, NALL>(lv);
        float2 ov[8]; float lw[8];
#pragma unroll
        for (int w = 0; w < 8; w++) { ov[w] = lds64(src + w * 2176); lw[w] = lds32(s_ml + 128 + (w * 4 + h) * 4); }
        const float a0 = ((ov[0].x + ov[1].x) + (ov[2].x + ov[3].x)) + ((ov[4].x + ov[5].x) + (ov[6].x + ov[7].x));
        const float a1 = ((ov[0].y + ov[1].y) + (ov[2].y + ov[3].y)) + ((ov[4].y + ov[5].y) + (ov[6].y + ov[7].y));
        const float L = ((lw[0] + lw[1]) + (lw[2] + lw[3])) + ((lw[4] + lw[5]) + (lw[6] + lw[7]));
        st_tag2(p_po, a0, a1, tag, lv);
        st_tag2(p_pml, Mh, L, tag, lv && (vtid & 63) == 0);
        bar_arrive_p<11, NALL>(lv);
    }
    {
        const int slot = (ITEM_WO + wg) % NSLOT;
        mbar_wait_p(sbase + SM_WBAR + 8 * (2 * wg), 0, lv);
        mbar_wait_p(sbase + SM_WBAR + 8 * (2 * wg + 1), 0, lv);
        const int krow = (lane & 7) + ((lane >> 4) << 3);
        const uint32_t wb = sbase + slot * SLOT_BYTES + krow * 128 + ((((wl << 1) + ((lane >> 3) & 1)) ^ (krow & 7)) << 4);
        uint32_t a[8][4];
#pragma unroll
        for (int ks = 0; ks < 8; ks++) ldsm4t(a[ks], wb + ks * 2048);
        uint32_t sb = s_of + brow * 272 + bch * 16;
        pin(sb);
        bar_sync_p<3, NALL>(lv);
        uint32_t b[4][4];
#pragma unroll
        for (int kp = 0; kp < 4; kp++) ldsm4(b[kp], sb + kp * 64);
        float acc[4][4] = {};
#pragma unroll
        for (int kp = 0; kp < 4; kp++) {
            mma16816(acc[kp], a[2 * kp], b[kp][0], b[kp][1]);
            mma16816(acc[kp], a[2 * kp + 1], b[kp][2], b[kp][3]);
        }
        st_tag2(p_in1, (acc[0][0] + acc[1][0]) + (acc[2][0] + acc[3][0]), (acc[0][1] + acc[1][1]) + (acc[2][1] + acc[3][1]), tag, pw);
        st_tag2(p_in1 + 32 * 16, (acc[0][2] + acc[1][2]) + (acc[2][2] + acc[3][2]), (acc[0][3] + acc[1][3]) + (acc[2][3] + acc[3][3]), tag, pw);
        bar_arrive_p<8, NCONS + 32>(lv);
    }
    if (c < NFCTA) {
        uint32_t ag[4][4], au[4][4], ad[4][4];
        {
            const int slot = (ITEM_GU + wg) % NSLOT;
            mbar_wait_p(sbase + SM_WBAR + 8 * (4 + 2 * wg), 0, lv);
            mbar_wait_p(sbase + SM_WBAR + 8 * (5 + 2 * wg), 0, lv);
            const int krow = wl * 64 + (lane & 7) + ((lane >> 4) << 3);
            const uint32_t gb = sbase + slot * SLOT_BYTES + krow * 32 + ((((lane >> 3) & 1) ^ ((krow >> 2) & 1)) << 4);
#pragma unroll
            for (int ks = 0; ks < 4; ks++) { ldsm4t(ag[ks], gb + ks * 512); ldsm4t(au[ks], gb + 8192 + ks * 512); }
        }
        uint32_t sb = s_xn + brow * 1040 + (warp * 64 + bch * 8) * 2;
        uint32_t sd = s_red + (warp * 160 + (2 * t4) * 20 + r) * 4;
        uint32_t sa = s_act + brow * 48 + (bch & 1) * 16;
        pin(sb); pin(sd); pin(sa);
        bar_sync_p<4, NALL>(lv);
        {
            uint32_t b0[4], b1[4];
            ldsm4(b0, sb); ldsm4(b1, sb + 64);
            float g0[4] = {}, g1[4] = {}, u0[4] = {}, u1[4] = {};
            mma16816(g0, ag[0], b0[0], b0[1]); mma16816(u0, au[0], b0[0], b0[1]);
            mma16816(g1, ag[2], b1[0], b1[1]); mma16816(u1, au[2], b1[0], b1[1]);
            mma16816(g0, ag[1], b0[2], b0[3]); mma16816(u0, au[1], b0[2], b0[3]);
            mma16816(g1, ag[3], b1[2], b1[3]); mma16816(u1, au[3], b1[2], b1[3]);
            sts32(sd, g0[0] + g1[0], pw);        sts32(sd + 80, g0[1] + g1[1], pw);
            sts32(sd + 32, g0[2] + g1[2], pw);   sts32(sd + 80 + 32, g0[3] + g1[3], pw);
            sts32(sd + 320, u0[0] + u1[0], pw);      sts32(sd + 320 + 80, u0[1] + u1[1], pw);
            sts32(sd + 320 + 32, u0[2] + u1[2], pw); sts32(sd + 320 + 80 + 32, u0[3] + u1[3], pw);
            bar_arrive_p<5, NCONS + 64>(lv);
        }
        {
            const int slot = (ITEM_WD + wg) % NSLOT;
            mbar_wait_p(sbase + SM_WBAR + 8 * (8 + wg), 0, lv);
            const int krow = (lane & 7) + ((lane >> 4) << 3);
            const uint32_t db = sbase + slot * SLOT_BYTES + wl * 2048 + krow * 128;
#pragma unroll
            for (int j = 0; j < 4; j++) ldsm4t(ad[j], db + (((2 * j + ((lane >> 3) & 1)) ^ (krow & 7)) << 4));
            bar_sync_p<6, NCONS + 64>(lv);
            uint32_t b[4];
            ldsm4(b, sa);
#pragma unroll
            for (int j = 0; j < 4; j++) {
                float acc[4] = {0.f, 0.f, 0.f, 0.f};
                mma16816(acc, ad[j], b[0], b[1]);
                st_tag2(p_in2 + (2 * j) * NFCTA * 16, acc[0], acc[1], tag, pw);
                st_tag2(p_in2 + (2 * j + 1) * NFCTA * 16, acc[2], acc[3], tag, pw);
            }
            bar_arrive_p<9, NALL>(lv);
        }
    }
    if (lv) return;

    {
        const int hw = (tid >> 5) - 9;
        const int red_b = 2 * (c >> 6) + ((lane >> 3) & 1);
        const int red_n = 8 * (c & 63) + 2 * t4 + ((lane >> 4) & 1);
        const float x_res = __bfloat162float(x[red_b * DM + red_n]);
        const int cta0 = (hw * 8 + (c >> 4)) * 4, hh = (c >> 2) & 3;
        const float* q_po = &g_po[(cta0 * 4 + hh) * DH + lane * 4];
        const float* q_pml = &g_pml[(cta0 * 4 + hh) * 2];
        const float* q_in1 = &g_in1[(c * 32 + r) * 16 + 4 * t4];
        float* p_h = &g_h[((lane & 4) ? HREP / 2 : 0) * (NB * DM) + red_b * DM + red_n];
        const float* q_h = &g_h[(c % HREP) * (NB * DM) + hw * DM + lane * 4];
        const float* q_in2 = &g_in2[(c * NFCTA + r) * 16 + 4 * t4];
        __nv_bfloat16* p_out = out + red_b * DM + red_n;
        uint32_t s_ofw = s_of + (hw * 136 + lane * 4) * 2, s_hn = s_xn + hw * 1040 + lane * 8;
        uint32_t s_gu = s_red + (((hw & 1) * 2 + (lane >> 4)) * 20 + (lane & 15)) * 4;
        uint32_t s_actw = s_act + (((hw & 1) * 2 + (lane >> 4)) * 24 + (lane & 15)) * 2;
        uint32_t s_fin = s_of + lane * 4;
        pin(s_fin);
        pin(q_po); pin(q_pml); pin(q_in1); pin(p_h); pin(q_h); pin(q_in2); pin(p_out); pin(s_ofw); pin(s_hn); pin(s_gu); pin(s_actw);

#pragma unroll 1
        for (int pass = 0; pass < 2; pass++) {
            asm volatile("mov.u32 %0, %1;" : "=r"(lv) : "r"(pass));
            if (lv) {
                if (hw == 0) {
                    uint32_t it = 0;
                    while (true) {
                        const int seen = (int)(ld_rlx1(&g_count) - epoch * NCTA);
                        if (lane == 0) asm volatile("st.volatile.shared.u32 [%0], %1;" ::"r"(sbase + SM_CNT), "r"(seen) : "memory");
                        if (seen >= NCTA) break;
                        __nanosleep(seen > 0 ? 100 : 1000);
                        if (++it > SPIN_LIMIT) __trap();
                    }
                }
                asm volatile("bar.sync 10, 128;" ::: "memory");
                asm volatile("bar.sync 11, 384;" ::: "memory");
                spin_cycles(POLL_DELAY1);
            }
            {
                PollSet<4, 4 * DH, 4, 8> ps;
                poll1(ps, q_po, q_pml, tag, lv);
                const uint4 (&ov)[4] = ps.v;
                const uint2 (&ml)[4] = ps.m;
                const float M = fmaxf(fmaxf(untag(ml[0].x), untag(ml[1].x)), fmaxf(untag(ml[2].x), untag(ml[3].x)));
                const float e0 = ex2((untag(ml[0].x) - M) * LOG2E), e1 = ex2((untag(ml[1].x) - M) * LOG2E);
                const float e2 = ex2((untag(ml[2].x) - M) * LOG2E), e3 = ex2((untag(ml[3].x) - M) * LOG2E);
                const float inv = rcp_approx(fmaf(e0, untag(ml[0].y), e1 * untag(ml[1].y)) + fmaf(e2, untag(ml[2].y), e3 * untag(ml[3].y)));
                const float a0 = fmaf(e0, untag(ov[0].x), e1 * untag(ov[1].x)) + fmaf(e2, untag(ov[2].x), e3 * untag(ov[3].x));
                const float a1 = fmaf(e0, untag(ov[0].y), e1 * untag(ov[1].y)) + fmaf(e2, untag(ov[2].y), e3 * untag(ov[3].y));
                const float a2 = fmaf(e0, untag(ov[0].z), e1 * untag(ov[1].z)) + fmaf(e2, untag(ov[2].z), e3 * untag(ov[3].z));
                const float a3 = fmaf(e0, untag(ov[0].w), e1 * untag(ov[1].w)) + fmaf(e2, untag(ov[2].w), e3 * untag(ov[3].w));
                sts64(s_ofw, pack_bf16(a0 * inv, a1 * inv), pack_bf16(a2 * inv, a3 * inv), lv);
                bar_arrive_p<3, NALL>(lv);
            }
            float h_res = 0.f;
            if (hw == 3 || !lv) {
                bar_sync_p<8, NCONS + 32>(lv);
                if (lv) spin_cycles(POLL_DELAY);
                const float kk = inbox_reduce<false>(q_in1, tag, lv, lane);
                h_res = bf16r(x_res + bf16r(kk));
#pragma unroll
                for (int rp = 0; rp < HREP / 2; rp++) st_tag1(p_h + rp * (NB * DM), h_res, tag, lv);
                bar_arrive_p<7, 128>(lv);
            }
            if (hw != 3) bar_sync_p<7, 128>(lv);
            if (lv) spin_cycles(POLL_DELAY);
            if (c < NFCTA) {
                PollSet<4, 128, 0, 0> ps;
                poll1(ps, q_h, q_h, tag, lv);
                const uint4 (&u)[4] = ps.v;
                float v[16];
#pragma unroll
                for (int k = 0; k < 4; k++) {
                    v[4 * k + 0] = u2f(u[k].x & 0xffff0000u); v[4 * k + 1] = u2f(u[k].y & 0xffff0000u);
                    v[4 * k + 2] = u2f(u[k].z & 0xffff0000u); v[4 * k + 3] = u2f(u[k].w & 0xffff0000u);
                }
                warp_layernorm_store(v, __shfl_sync(0xffffffffu, v[0], 0), s_hn, lv);
                bar_arrive_p<4, NALL>(lv);
                if (hw < 2 || !lv) {
                    bar_sync_p<5, NCONS + 64>(lv);
                    float gw[8], uw[8];
#pragma unroll
                    for (int w = 0; w < 8; w++) { gw[w] = lds32(s_gu + w * 640); uw[w] = lds32(s_gu + w * 640 + 320); }
                    const float g = bf16r(((gw[0] + gw[1]) + (gw[2] + gw[3])) + ((gw[4] + gw[5]) + (gw[6] + gw[7])));
                    const float u_ = bf16r(((uw[0] + uw[1]) + (uw[2] + uw[3])) + ((uw[4] + uw[5]) + (uw[6] + uw[7])));
                    const float inner = 0.7978845608028654f * fmaf(0.044715f * g * g, g, g);
                    const float ge = bf16r(__fdividef(g, 1.f + __expf(-2.f * inner)));
                    sts16(s_actw, __bfloat16_as_ushort(__float2bfloat16_rn(ge * u_)), lv);
                    bar_arrive_p<6, NCONS + 64>(lv);
                }
            }
            if (c < NFCTA) bar_sync_p<9, NALL>(lv);
            if (lv) spin_cycles(POLL_DELAY);
            const float k2p = inbox_reduce<true>(q_in2 + hw * 28 * 16, tag, lv, lane);
            sts32(s_fin + hw * 128, k2p, lv);
            if (hw != 3) bar_arrive_p<12, 128>(lv);
            if (hw == 3 || !lv) {
                bar_sync_p<12, 128>(lv);
                const float k2 = (lds32(s_fin) + lds32(s_fin + 128)) + (lds32(s_fin + 256) + lds32(s_fin + 384));
                if (lv && !(lane & 4)) *p_out = __float2bfloat16_rn(h_res + bf16r(k2));
                if (lv && c == 0 && lane == 0) {
                    asm volatile("st.relaxed.gpu.global.u32 [%0], %1;" ::"l"(&g_epoch), "r"(epoch + 1) : "memory");
                }
            }
        }
    }
}

typedef CUresult (*EncodeFn)(CUtensorMap*, CUtensorMapDataType, cuuint32_t, void*, const cuuint64_t*, const cuuint64_t*,
                             const cuuint32_t*, const cuuint32_t*, CUtensorMapInterleave, CUtensorMapSwizzle,
                             CUtensorMapL2promotion, CUtensorMapFloatOOBfill);

CUtensorMap make_map(EncodeFn enc, const void* base, int rank, const cuuint64_t* dims, const cuuint64_t* strides,
                     const cuuint32_t* box, CUtensorMapSwizzle sw, CUtensorMapL2promotion promo) {
    CUtensorMap tm;
    cuuint32_t es[3] = {1, 1, 1};
    enc(&tm, CU_TENSOR_MAP_DATA_TYPE_BFLOAT16, rank, const_cast<void*>(base), dims, strides, box, es,
        CU_TENSOR_MAP_INTERLEAVE_NONE, sw, promo, CU_TENSOR_MAP_FLOAT_OOB_FILL_NONE);
    return tm;
}

}

extern "C" void kernel_launch(void* const* d_in, const int* in_sizes, int n_in, void* d_out, int out_size) {
    (void)in_sizes; (void)n_in; (void)out_size;
    const void* x = d_in[0];
    const void* kc = d_in[1];
    const void* vc = d_in[2];
    const void* wq = d_in[3];
    const void* wo = d_in[4];
    const void* wg = d_in[6];
    const void* wu = d_in[7];
    const void* wd = d_in[8];

    static EncodeFn enc = nullptr;
    if (!enc) {
        void* fn = nullptr;
        cudaDriverEntryPointQueryResult qr;
        cudaGetDriverEntryPoint("cuTensorMapEncodeTiled", &fn, cudaEnableDefault, &qr);
        enc = reinterpret_cast<EncodeFn>(fn);
        cudaFuncSetAttribute(fused_decode_kernel, cudaFuncAttributeMaxDynamicSharedMemorySize, SMEM_BYTES);
    }
    const auto P256 = CU_TENSOR_MAP_L2_PROMOTION_L2_256B;
    CUtensorMap tmK, tmV, tmWq, tmWo, tmWg, tmWu, tmWd;
    {
        cuuint64_t dims[3] = {64, (cuuint64_t)NB * HKV * SK, 2};
        cuuint64_t str[2] = {256, 128};
        cuuint32_t box[3] = {64, 64, 2};
        tmK = make_map(enc, kc, 3, dims, str, box, CU_TENSOR_MAP_SWIZZLE_128B, P256);
        tmV = make_map(enc, vc, 3, dims, str, box, CU_TENSOR_MAP_SWIZZLE_128B, P256);
    }
    {
        cuuint64_t dims[2] = {HQ * DH, DM};
        cuuint64_t str[1] = {HQ * DH * 2};
        cuuint32_t box[2] = {32, 256};
        tmWq = make_map(enc, wq, 2, dims, str, box, CU_TENSOR_MAP_SWIZZLE_64B, P256);
    }
    {
        cuuint64_t dims[3] = {64, HQ * DH, 8};
        cuuint64_t str[2] = {DM * 2, 128};
        cuuint32_t box[3] = {64, 64, 1};
        tmWo = make_map(enc, wo, 3, dims, str, box, CU_TENSOR_MAP_SWIZZLE_128B, P256);
    }
    {
        cuuint64_t dims[2] = {FF, DM};
        cuuint64_t str[1] = {FF * 2};
        cuuint32_t box[2] = {16, 256};
        tmWg = make_map(enc, wg, 2, dims, str, box, CU_TENSOR_MAP_SWIZZLE_32B, P256);
        tmWu = make_map(enc, wu, 2, dims, str, box, CU_TENSOR_MAP_SWIZZLE_32B, P256);
    }
    {
        cuuint64_t dims[3] = {64, FF, 8};
        cuuint64_t str[2] = {DM * 2, 128};
        cuuint32_t box[3] = {64, 16, 4};
        tmWd = make_map(enc, wd, 3, dims, str, box, CU_TENSOR_MAP_SWIZZLE_128B, P256);
    }
    fused_decode_kernel<<<NCTA, NTHREADS, SMEM_BYTES, cudaStreamPerThread>>>(
        tmK, tmV, tmWq, tmWo, tmWg, tmWu, tmWd, (const __nv_bfloat16*)x, (__nv_bfloat16*)d_out);
}
```
